```python
import torch

def _softmax(x, axis=-1):
    return torch.softmax(x, dim=axis)
def _gelu(x):
    return torch.nn.functional.gelu(x, approximate="tanh")
def _silu(x):
    return torch.nn.functional.silu(x)
def _sigmoid(x):
    return torch.sigmoid(x)
def _layernorm(x, axis=-1, eps=1e-5):
    m = x.mean(dim=axis, keepdim=True)
    v = x.var(dim=axis, keepdim=True, unbiased=False)
    return (x - m) / torch.sqrt(v + eps)
def _scatter_add(tgt, idx, src, axis=0):
    return tgt.clone().index_add_(axis, idx, src)
def _segment_sum(src, seg, n):
    out = torch.zeros((n,) + src.shape[1:], dtype=src.dtype)
    return out.index_add_(0, seg, src)
def _pad(x, pw):
    flat = tuple(v for pair in reversed(pw) for v in pair)
    return torch.nn.functional.pad(x, flat)

kernel_name = 'gated_mix__sliding_local_dilated__mha_block__prompt'

def setup_inputs():

    _w = (lambda a: (lambda t: t.to(torch.bfloat16) if t.is_floating_point() else t)(torch.as_tensor(a)))
    def _A_setup():
        B, S, D = 1, 2048, 640
        return {
            "x": _w((lambda *s: torch.randn(*s, dtype=torch.bfloat16) * 0.05)(B, S, D)),
            "wqkv": _w((lambda *s: torch.randn(*s, dtype=torch.bfloat16) * 1.6)(D, 3 * D)),
            "wo": _w((lambda *s: torch.randn(*s, dtype=torch.bfloat16) * 0.05)(D, D)),
        }
    _A_in = _A_setup()

    def _B_setup():
        B, S, D, H = 1, 2048, 640, 32
        return {
            "x": _w((lambda *s: torch.randn(*s, dtype=torch.bfloat16) * 0.05)(B, S, D)),
            "wqkv": _w((lambda *s: torch.randn(*s, dtype=torch.bfloat16) * 1.6)(D, 3 * D)),
            "wo": _w((lambda *s: torch.randn(*s, dtype=torch.bfloat16) * 0.1)(D, D)),
        }
    _B_in = _B_setup()

    return {
        "A_x": _A_in["x"],
        "A_wqkv": _A_in["wqkv"],
        "A_wo": _A_in["wo"],
        "B_x": _B_in["x"],
        "B_wqkv": _B_in["wqkv"],
        "B_wo": _B_in["wo"],
        "gate_w": _w((lambda *s: torch.randn(*s, dtype=torch.bfloat16) * 0.05)(640) * 16.0),
    }

def reference(A_x, A_wqkv, A_wo, B_x, B_wqkv, B_wo, gate_w):
    def _A_ref(x, wqkv, wo):
        B, S, D = x.shape
        H = 32; Dh = D // H
        W, dil = 8, 2
        qkv = (lambda x, *d: x.permute(*d))((x @ wqkv).reshape(B, S, 3, H, Dh), 2, 0, 3, 1, 4)
        q, k, v = qkv[0], qkv[1], qkv[2]
        scale = Dh ** -0.5
        pos = torch.arange(S)
        off = torch.arange(W) * dil
        idx = pos[:, None] - off[None, :]
        mask = idx >= 0
        idx_c = torch.where(mask, idx, 0).reshape(-1)
        kg = k[:, :, idx_c, :].reshape(B, H, S, W, Dh)
        vg = v[:, :, idx_c, :].reshape(B, H, S, W, Dh)
        logits = torch.einsum("bhsd,bhswd->bhsw", q, kg) * scale
        logits = torch.where(mask[None, None, :, :], logits, -1e9)
        attn = _softmax(logits, axis=-1)
        o = torch.einsum("bhsw,bhswd->bhsd", attn, vg)
        return (lambda x, *d: x.permute(*d))(o, 0, 2, 1, 3).reshape(B, S, D) @ wo

    def _B_ref(x, wqkv, wo):
        B, S, D = x.shape
        H = 32
        Dh = D // H
        qkv = (lambda x, *d: x.permute(*d))((x @ wqkv).reshape(B, S, 3, H, Dh), 2, 0, 3, 1, 4)
        q, k, v = qkv[0], qkv[1], qkv[2]
        scores = torch.einsum("bhqd,bhkd->bhqk", q, k) * (Dh ** -0.5)
        p = _softmax(scores, axis=-1)
        o = torch.einsum("bhqk,bhkd->bhqd", p, v)
        return (lambda x, *d: x.permute(*d))(o, 0, 2, 1, 3).reshape(B, S, D) @ wo

    x = A_x
    g = _sigmoid((x * gate_w).sum(-1, keepdims=True))
    a = _A_ref(x, A_wqkv, A_wo)
    b = _B_ref(x, B_wqkv, B_wo)
    return g * a + (1 - g) * b
```

```cpp
#include <cuda_runtime.h>
#include <cuda_bf16.h>
#include <cuda.h>
#include <stdint.h>

constexpr int SEQ = 2048, DM = 640, NH = 32;
constexpr int XHEAD = 256 * 384;
constexpr int XPART = NH * XHEAD;

__device__ __align__(1024) uint8_t g_XB[3 * XPART];
__device__ uint32_t g_HB[16 * 16 * 25 * 32];
__device__ __align__(128) uint32_t g_cnt[18][32];
__device__ __align__(1024) uint32_t g_O[2 * 32 * 80 * 256];
__device__ __align__(1024) uint4 g_Wo[2 * 8 * 6400];
__device__ __align__(1024) uint4 g_Wg[640 * 64];
__device__ uint32_t g_gcnt;
__device__ float2 g_gate[SEQ];
__device__ float g_nmax[2][8][128];

#define POLY_PAT 0xABABABABu
__host__ __device__ constexpr bool is_poly(int blk) { return (POLY_PAT >> (blk & 31)) & 1; }

#define TS(k, i)
#define TSA(k, i)
#define TSA_DUMP(k)
#define TSB(i)

template<int TB> __device__ __forceinline__ void wgmma_rs_n24(float (&d)[12], uint32_t a0, uint32_t a1, uint32_t a2, uint32_t a3, uint64_t db, int sd) {
  asm volatile("{\n.reg .pred p;\nsetp.ne.b32 p, %17, 0;\n"
    "wgmma.mma_async.sync.aligned.m64n24k16.f32.bf16.bf16 {%0, %1, %2, %3, %4, %5, %6, %7, %8, %9, %10, %11}, {%12, %13, %14, %15}, %16, p, 1, 1, %18;\n}\n"
    : "+f"(d[0]), "+f"(d[1]), "+f"(d[2]), "+f"(d[3]), "+f"(d[4]), "+f"(d[5]), "+f"(d[6]), "+f"(d[7]), "+f"(d[8]), "+f"(d[9]), "+f"(d[10]), "+f"(d[11])
    : "r"(a0), "r"(a1), "r"(a2), "r"(a3), "l"(db), "r"(sd), "n"(TB));
}
template<int TB> __device__ __forceinline__ void wgmma_rs_n32(float (&d)[16], uint32_t a0, uint32_t a1, uint32_t a2, uint32_t a3, uint64_t db, int sd) {
  asm volatile("{\n.reg .pred p;\nsetp.ne.b32 p, %21, 0;\n"
    "wgmma.mma_async.sync.aligned.m64n32k16.f32.bf16.bf16 {%0, %1, %2, %3, %4, %5, %6, %7, %8, %9, %10, %11, %12, %13, %14, %15}, {%16, %17, %18, %19}, %20, p, 1, 1, %22;\n}\n"
    : "+f"(d[0]), "+f"(d[1]), "+f"(d[2]), "+f"(d[3]), "+f"(d[4]), "+f"(d[5]), "+f"(d[6]), "+f"(d[7]), "+f"(d[8]), "+f"(d[9]), "+f"(d[10]), "+f"(d[11]), "+f"(d[12]), "+f"(d[13]), "+f"(d[14]), "+f"(d[15])
    : "r"(a0), "r"(a1), "r"(a2), "r"(a3), "l"(db), "r"(sd), "n"(TB));
}
template<int TB> __device__ __forceinline__ void wgmma_rs_n32_z(float (&d)[16], uint32_t a0, uint32_t a1, uint32_t a2, uint32_t a3, uint64_t db) {
  asm volatile("wgmma.mma_async.sync.aligned.m64n32k16.f32.bf16.bf16 {%0, %1, %2, %3, %4, %5, %6, %7, %8, %9, %10, %11, %12, %13, %14, %15}, {%16, %17, %18, %19}, %20, 0, 1, 1, %21;\n"
    : "=f"(d[0]), "=f"(d[1]), "=f"(d[2]), "=f"(d[3]), "=f"(d[4]), "=f"(d[5]), "=f"(d[6]), "=f"(d[7]), "=f"(d[8]), "=f"(d[9]), "=f"(d[10]), "=f"(d[11]), "=f"(d[12]), "=f"(d[13]), "=f"(d[14]), "=f"(d[15])
    : "r"(a0), "r"(a1), "r"(a2), "r"(a3), "l"(db), "n"(TB));
}
template<int TB> __device__ __forceinline__ void wgmma_rs_n64(float (&d)[32], uint32_t a0, uint32_t a1, uint32_t a2, uint32_t a3, uint64_t db, int sd) {
  asm volatile("{\n.reg .pred p;\nsetp.ne.b32 p, %37, 0;\n"
    "wgmma.mma_async.sync.aligned.m64n64k16.f32.bf16.bf16 {%0, %1, %2, %3, %4, %5, %6, %7, %8, %9, %10, %11, %12, %13, %14, %15, %16, %17, %18, %19, %20, %21, %22, %23, %24, %25, %26, %27, %28, %29, %30, %31}, {%32, %33, %34, %35}, %36, p, 1, 1, %38;\n}\n"
    : "+f"(d[0]), "+f"(d[1]), "+f"(d[2]), "+f"(d[3]), "+f"(d[4]), "+f"(d[5]), "+f"(d[6]), "+f"(d[7]), "+f"(d[8]), "+f"(d[9]), "+f"(d[10]), "+f"(d[11]), "+f"(d[12]), "+f"(d[13]), "+f"(d[14]), "+f"(d[15]), "+f"(d[16]), "+f"(d[17]), "+f"(d[18]), "+f"(d[19]), "+f"(d[20]), "+f"(d[21]), "+f"(d[22]), "+f"(d[23]), "+f"(d[24]), "+f"(d[25]), "+f"(d[26]), "+f"(d[27]), "+f"(d[28]), "+f"(d[29]), "+f"(d[30]), "+f"(d[31])
    : "r"(a0), "r"(a1), "r"(a2), "r"(a3), "l"(db), "r"(sd), "n"(TB));
}
template<int TB> __device__ __forceinline__ void wgmma_rs_n64_z(float (&d)[32], uint32_t a0, uint32_t a1, uint32_t a2, uint32_t a3, uint64_t db) {
  asm volatile("wgmma.mma_async.sync.aligned.m64n64k16.f32.bf16.bf16 {%0, %1, %2, %3, %4, %5, %6, %7, %8, %9, %10, %11, %12, %13, %14, %15, %16, %17, %18, %19, %20, %21, %22, %23, %24, %25, %26, %27, %28, %29, %30, %31}, {%32, %33, %34, %35}, %36, 0, 1, 1, %37;\n"
    : "=f"(d[0]), "=f"(d[1]), "=f"(d[2]), "=f"(d[3]), "=f"(d[4]), "=f"(d[5]), "=f"(d[6]), "=f"(d[7]), "=f"(d[8]), "=f"(d[9]), "=f"(d[10]), "=f"(d[11]), "=f"(d[12]), "=f"(d[13]), "=f"(d[14]), "=f"(d[15]), "=f"(d[16]), "=f"(d[17]), "=f"(d[18]), "=f"(d[19]), "=f"(d[20]), "=f"(d[21]), "=f"(d[22]), "=f"(d[23]), "=f"(d[24]), "=f"(d[25]), "=f"(d[26]), "=f"(d[27]), "=f"(d[28]), "=f"(d[29]), "=f"(d[30]), "=f"(d[31])
    : "r"(a0), "r"(a1), "r"(a2), "r"(a3), "l"(db), "n"(TB));
}
template<int TA, int TB> __device__ __forceinline__ void wgmma_ss_n240(float (&d)[120], uint64_t da, uint64_t db, int sd) {
  asm volatile("{\n.reg .pred p;\nsetp.ne.b32 p, %122, 0;\n"
    "wgmma.mma_async.sync.aligned.m64n240k16.f32.bf16.bf16 {%0, %1, %2, %3, %4, %5, %6, %7, %8, %9, %10, %11, %12, %13, %14, %15, %16, %17, %18, %19, %20, %21, %22, %23, %24, %25, %26, %27, %28, %29, %30, %31, %32, %33, %34, %35, %36, %37, %38, %39, %40, %41, %42, %43, %44, %45, %46, %47, %48, %49, %50, %51, %52, %53, %54, %55, %56, %57, %58, %59, %60, %61, %62, %63, %64, %65, %66, %67, %68, %69, %70, %71, %72, %73, %74, %75, %76, %77, %78, %79, %80, %81, %82, %83, %84, %85, %86, %87, %88, %89, %90, %91, %92, %93, %94, %95, %96, %97, %98, %99, %100, %101, %102, %103, %104, %105, %106, %107, %108, %109, %110, %111, %112, %113, %114, %115, %116, %117, %118, %119}, %120, %121, p, 1, 1, %123, %124;\n}\n"
    : "+f"(d[0]), "+f"(d[1]), "+f"(d[2]), "+f"(d[3]), "+f"(d[4]), "+f"(d[5]), "+f"(d[6]), "+f"(d[7]), "+f"(d[8]), "+f"(d[9]), "+f"(d[10]), "+f"(d[11]), "+f"(d[12]), "+f"(d[13]), "+f"(d[14]), "+f"(d[15]), "+f"(d[16]), "+f"(d[17]), "+f"(d[18]), "+f"(d[19]), "+f"(d[20]), "+f"(d[21]), "+f"(d[22]), "+f"(d[23]), "+f"(d[24]), "+f"(d[25]), "+f"(d[26]), "+f"(d[27]), "+f"(d[28]), "+f"(d[29]), "+f"(d[30]), "+f"(d[31]), "+f"(d[32]), "+f"(d[33]), "+f"(d[34]), "+f"(d[35]), "+f"(d[36]), "+f"(d[37]), "+f"(d[38]), "+f"(d[39]), "+f"(d[40]), "+f"(d[41]), "+f"(d[42]), "+f"(d[43]), "+f"(d[44]), "+f"(d[45]), "+f"(d[46]), "+f"(d[47]), "+f"(d[48]), "+f"(d[49]), "+f"(d[50]), "+f"(d[51]), "+f"(d[52]), "+f"(d[53]), "+f"(d[54]), "+f"(d[55]), "+f"(d[56]), "+f"(d[57]), "+f"(d[58]), "+f"(d[59]), "+f"(d[60]), "+f"(d[61]), "+f"(d[62]), "+f"(d[63]), "+f"(d[64]), "+f"(d[65]), "+f"(d[66]), "+f"(d[67]), "+f"(d[68]), "+f"(d[69]), "+f"(d[70]), "+f"(d[71]), "+f"(d[72]), "+f"(d[73]), "+f"(d[74]), "+f"(d[75]), "+f"(d[76]), "+f"(d[77]), "+f"(d[78]), "+f"(d[79]), "+f"(d[80]), "+f"(d[81]), "+f"(d[82]), "+f"(d[83]), "+f"(d[84]), "+f"(d[85]), "+f"(d[86]), "+f"(d[87]), "+f"(d[88]), "+f"(d[89]), "+f"(d[90]), "+f"(d[91]), "+f"(d[92]), "+f"(d[93]), "+f"(d[94]), "+f"(d[95]), "+f"(d[96]), "+f"(d[97]), "+f"(d[98]), "+f"(d[99]), "+f"(d[100]), "+f"(d[101]), "+f"(d[102]), "+f"(d[103]), "+f"(d[104]), "+f"(d[105]), "+f"(d[106]), "+f"(d[107]), "+f"(d[108]), "+f"(d[109]), "+f"(d[110]), "+f"(d[111]), "+f"(d[112]), "+f"(d[113]), "+f"(d[114]), "+f"(d[115]), "+f"(d[116]), "+f"(d[117]), "+f"(d[118]), "+f"(d[119])
    : "l"(da), "l"(db), "r"(sd), "n"(TA), "n"(TB));
}
template<int TA, int TB> __device__ __forceinline__ void wgmma_ss_n80(float (&d)[40], uint64_t da, uint64_t db, int sd) {
  asm volatile("{\n.reg .pred p;\nsetp.ne.b32 p, %42, 0;\n"
    "wgmma.mma_async.sync.aligned.m64n80k16.f32.bf16.bf16 {%0, %1, %2, %3, %4, %5, %6, %7, %8, %9, %10, %11, %12, %13, %14, %15, %16, %17, %18, %19, %20, %21, %22, %23, %24, %25, %26, %27, %28, %29, %30, %31, %32, %33, %34, %35, %36, %37, %38, %39}, %40, %41, p, 1, 1, %43, %44;\n}\n"
    : "+f"(d[0]), "+f"(d[1]), "+f"(d[2]), "+f"(d[3]), "+f"(d[4]), "+f"(d[5]), "+f"(d[6]), "+f"(d[7]), "+f"(d[8]), "+f"(d[9]), "+f"(d[10]), "+f"(d[11]), "+f"(d[12]), "+f"(d[13]), "+f"(d[14]), "+f"(d[15]), "+f"(d[16]), "+f"(d[17]), "+f"(d[18]), "+f"(d[19]), "+f"(d[20]), "+f"(d[21]), "+f"(d[22]), "+f"(d[23]), "+f"(d[24]), "+f"(d[25]), "+f"(d[26]), "+f"(d[27]), "+f"(d[28]), "+f"(d[29]), "+f"(d[30]), "+f"(d[31]), "+f"(d[32]), "+f"(d[33]), "+f"(d[34]), "+f"(d[35]), "+f"(d[36]), "+f"(d[37]), "+f"(d[38]), "+f"(d[39])
    : "l"(da), "l"(db), "r"(sd), "n"(TA), "n"(TB));
}
template<int TB> __device__ __forceinline__ void wgmma_rs_n80(float (&d)[40], uint32_t a0, uint32_t a1, uint32_t a2, uint32_t a3, uint64_t db, int sd) {
  asm volatile("{\n.reg .pred p;\nsetp.ne.b32 p, %45, 0;\n"
    "wgmma.mma_async.sync.aligned.m64n80k16.f32.bf16.bf16 {%0, %1, %2, %3, %4, %5, %6, %7, %8, %9, %10, %11, %12, %13, %14, %15, %16, %17, %18, %19, %20, %21, %22, %23, %24, %25, %26, %27, %28, %29, %30, %31, %32, %33, %34, %35, %36, %37, %38, %39}, {%40, %41, %42, %43}, %44, p, 1, 1, %46;\n}\n"
    : "+f"(d[0]), "+f"(d[1]), "+f"(d[2]), "+f"(d[3]), "+f"(d[4]), "+f"(d[5]), "+f"(d[6]), "+f"(d[7]), "+f"(d[8]), "+f"(d[9]), "+f"(d[10]), "+f"(d[11]), "+f"(d[12]), "+f"(d[13]), "+f"(d[14]), "+f"(d[15]), "+f"(d[16]), "+f"(d[17]), "+f"(d[18]), "+f"(d[19]), "+f"(d[20]), "+f"(d[21]), "+f"(d[22]), "+f"(d[23]), "+f"(d[24]), "+f"(d[25]), "+f"(d[26]), "+f"(d[27]), "+f"(d[28]), "+f"(d[29]), "+f"(d[30]), "+f"(d[31]), "+f"(d[32]), "+f"(d[33]), "+f"(d[34]), "+f"(d[35]), "+f"(d[36]), "+f"(d[37]), "+f"(d[38]), "+f"(d[39])
    : "r"(a0), "r"(a1), "r"(a2), "r"(a3), "l"(db), "r"(sd), "n"(TB));
}
template<int TB> __device__ __forceinline__ void wgmma_rs_n80_z(float (&d)[40], uint32_t a0, uint32_t a1, uint32_t a2, uint32_t a3, uint64_t db) {
  asm volatile("wgmma.mma_async.sync.aligned.m64n80k16.f32.bf16.bf16 {%0, %1, %2, %3, %4, %5, %6, %7, %8, %9, %10, %11, %12, %13, %14, %15, %16, %17, %18, %19, %20, %21, %22, %23, %24, %25, %26, %27, %28, %29, %30, %31, %32, %33, %34, %35, %36, %37, %38, %39}, {%40, %41, %42, %43}, %44, 0, 1, 1, %45;\n"
    : "=f"(d[0]), "=f"(d[1]), "=f"(d[2]), "=f"(d[3]), "=f"(d[4]), "=f"(d[5]), "=f"(d[6]), "=f"(d[7]), "=f"(d[8]), "=f"(d[9]), "=f"(d[10]), "=f"(d[11]), "=f"(d[12]), "=f"(d[13]), "=f"(d[14]), "=f"(d[15]), "=f"(d[16]), "=f"(d[17]), "=f"(d[18]), "=f"(d[19]), "=f"(d[20]), "=f"(d[21]), "=f"(d[22]), "=f"(d[23]), "=f"(d[24]), "=f"(d[25]), "=f"(d[26]), "=f"(d[27]), "=f"(d[28]), "=f"(d[29]), "=f"(d[30]), "=f"(d[31]), "=f"(d[32]), "=f"(d[33]), "=f"(d[34]), "=f"(d[35]), "=f"(d[36]), "=f"(d[37]), "=f"(d[38]), "=f"(d[39])
    : "r"(a0), "r"(a1), "r"(a2), "r"(a3), "l"(db), "n"(TB));
}
template<int TA, int TB> __device__ __forceinline__ void wgmma_ss_n240_z(float (&d)[120], uint64_t da, uint64_t db) {
  asm volatile("wgmma.mma_async.sync.aligned.m64n240k16.f32.bf16.bf16 {%0, %1, %2, %3, %4, %5, %6, %7, %8, %9, %10, %11, %12, %13, %14, %15, %16, %17, %18, %19, %20, %21, %22, %23, %24, %25, %26, %27, %28, %29, %30, %31, %32, %33, %34, %35, %36, %37, %38, %39, %40, %41, %42, %43, %44, %45, %46, %47, %48, %49, %50, %51, %52, %53, %54, %55, %56, %57, %58, %59, %60, %61, %62, %63, %64, %65, %66, %67, %68, %69, %70, %71, %72, %73, %74, %75, %76, %77, %78, %79, %80, %81, %82, %83, %84, %85, %86, %87, %88, %89, %90, %91, %92, %93, %94, %95, %96, %97, %98, %99, %100, %101, %102, %103, %104, %105, %106, %107, %108, %109, %110, %111, %112, %113, %114, %115, %116, %117, %118, %119}, %120, %121, 0, 1, 1, %122, %123;\n"
    : "=f"(d[0]), "=f"(d[1]), "=f"(d[2]), "=f"(d[3]), "=f"(d[4]), "=f"(d[5]), "=f"(d[6]), "=f"(d[7]), "=f"(d[8]), "=f"(d[9]), "=f"(d[10]), "=f"(d[11]), "=f"(d[12]), "=f"(d[13]), "=f"(d[14]), "=f"(d[15]), "=f"(d[16]), "=f"(d[17]), "=f"(d[18]), "=f"(d[19]), "=f"(d[20]), "=f"(d[21]), "=f"(d[22]), "=f"(d[23]), "=f"(d[24]), "=f"(d[25]), "=f"(d[26]), "=f"(d[27]), "=f"(d[28]), "=f"(d[29]), "=f"(d[30]), "=f"(d[31]), "=f"(d[32]), "=f"(d[33]), "=f"(d[34]), "=f"(d[35]), "=f"(d[36]), "=f"(d[37]), "=f"(d[38]), "=f"(d[39]), "=f"(d[40]), "=f"(d[41]), "=f"(d[42]), "=f"(d[43]), "=f"(d[44]), "=f"(d[45]), "=f"(d[46]), "=f"(d[47]), "=f"(d[48]), "=f"(d[49]), "=f"(d[50]), "=f"(d[51]), "=f"(d[52]), "=f"(d[53]), "=f"(d[54]), "=f"(d[55]), "=f"(d[56]), "=f"(d[57]), "=f"(d[58]), "=f"(d[59]), "=f"(d[60]), "=f"(d[61]), "=f"(d[62]), "=f"(d[63]), "=f"(d[64]), "=f"(d[65]), "=f"(d[66]), "=f"(d[67]), "=f"(d[68]), "=f"(d[69]), "=f"(d[70]), "=f"(d[71]), "=f"(d[72]), "=f"(d[73]), "=f"(d[74]), "=f"(d[75]), "=f"(d[76]), "=f"(d[77]), "=f"(d[78]), "=f"(d[79]), "=f"(d[80]), "=f"(d[81]), "=f"(d[82]), "=f"(d[83]), "=f"(d[84]), "=f"(d[85]), "=f"(d[86]), "=f"(d[87]), "=f"(d[88]), "=f"(d[89]), "=f"(d[90]), "=f"(d[91]), "=f"(d[92]), "=f"(d[93]), "=f"(d[94]), "=f"(d[95]), "=f"(d[96]), "=f"(d[97]), "=f"(d[98]), "=f"(d[99]), "=f"(d[100]), "=f"(d[101]), "=f"(d[102]), "=f"(d[103]), "=f"(d[104]), "=f"(d[105]), "=f"(d[106]), "=f"(d[107]), "=f"(d[108]), "=f"(d[109]), "=f"(d[110]), "=f"(d[111]), "=f"(d[112]), "=f"(d[113]), "=f"(d[114]), "=f"(d[115]), "=f"(d[116]), "=f"(d[117]), "=f"(d[118]), "=f"(d[119])
    : "l"(da), "l"(db), "n"(TA), "n"(TB));
}

__device__ __forceinline__ void wg_fence() { asm volatile("wgmma.fence.sync.aligned;" ::: "memory"); }
__device__ __forceinline__ void wg_commit() { asm volatile("wgmma.commit_group.sync.aligned;" ::: "memory"); }
template<int N> __device__ __forceinline__ void wg_wait() { asm volatile("wgmma.wait_group.sync.aligned %0;" :: "n"(N) : "memory"); }
template<int N> __device__ __forceinline__ void fence_regs(float (&d)[N]) {
    #pragma unroll
    for (int i = 0; i < N; i++) asm volatile("" : "+f"(d[i]) :: "memory");
}
__device__ __forceinline__ uint64_t mkdesc(uint32_t addr, uint32_t lbo, uint32_t sbo, uint32_t swz) {
    return (uint64_t)((addr & 0x3FFFF) >> 4) | ((uint64_t)(lbo >> 4) << 16) | ((uint64_t)(sbo >> 4) << 32) | ((uint64_t)swz << 62);
}
__device__ __forceinline__ uint32_t smem_u32(const void* p) { return (uint32_t)__cvta_generic_to_shared(p); }
__device__ __forceinline__ void mbar_init(uint32_t a, uint32_t c) { asm volatile("mbarrier.init.shared::cta.b64 [%0], %1;" :: "r"(a), "r"(c)); }
__device__ __forceinline__ void mbar_expect(uint32_t a, uint32_t b) { asm volatile("mbarrier.arrive.expect_tx.shared::cta.b64 _, [%0], %1;" :: "r"(a), "r"(b) : "memory"); }
__device__ __forceinline__ void mbar_arrive(uint32_t a) { asm volatile("mbarrier.arrive.shared::cta.b64 _, [%0];" :: "r"(a) : "memory"); }
__device__ __forceinline__ void mbar_wait(uint32_t a, uint32_t ph) {
    asm volatile("{\n.reg .pred p;\n.reg .u32 n;\n"
                 "mbarrier.try_wait.parity.shared::cta.b64 p, [%0], %1;\n@p bra.uni LD;\nmov.u32 n, 0;\n"
                 "LW:\nmbarrier.try_wait.parity.shared::cta.b64 p, [%0], %1;\n@p bra.uni LD;\n"
                 "add.u32 n, n, 1;\nsetp.lt.u32 p, n, 1048576;\n@p bra.uni LW;\nLD:\n}" :: "r"(a), "r"(ph) : "memory");
}
template<int NS> __device__ __forceinline__ void mbar_wait_ns(uint32_t a, uint32_t ph) {
    asm volatile("{\n.reg .pred p;\n.reg .u32 n;\n"
                 "mbarrier.try_wait.parity.shared::cta.b64 p, [%0], %1;\n@p bra.uni LD;\nmov.u32 n, 0;\n"
                 "LW:\nnanosleep.u32 %2;\nmbarrier.try_wait.parity.shared::cta.b64 p, [%0], %1;\n@p bra.uni LD;\n"
                 "add.u32 n, n, 1;\nsetp.lt.u32 p, n, 1048576;\n@p bra.uni LW;\nLD:\n}" :: "r"(a), "r"(ph), "n"(NS) : "memory");
}
__device__ __forceinline__ void tma2d(uint32_t dst, const CUtensorMap* tm, uint32_t bar, int c0, int c1) {
    asm volatile("cp.async.bulk.tensor.2d.shared::cluster.global.mbarrier::complete_tx::bytes [%0], [%1, {%3, %4}], [%2];"
                 :: "r"(dst), "l"(tm), "r"(bar), "r"(c0), "r"(c1) : "memory");
}
__device__ __forceinline__ void tma2d_mc(uint32_t dst, const CUtensorMap* tm, uint32_t bar, int c0, int c1) {
    asm volatile("cp.async.bulk.tensor.2d.shared::cluster.global.mbarrier::complete_tx::bytes.multicast::cluster [%0], [%1, {%3, %4}], [%2], %5;"
                 :: "r"(dst), "l"(tm), "r"(bar), "r"(c0), "r"(c1), "h"((uint16_t)3) : "memory");
}
__device__ __forceinline__ void mbar_arrive_cluster(uint32_t a) { asm volatile("mbarrier.arrive.shared::cluster.b64 _, [%0];" :: "r"(a) : "memory"); }
__device__ __forceinline__ void bulk_g2s(uint32_t dst, const void* src, uint32_t bytes, uint32_t bar) {
    asm volatile("cp.async.bulk.shared::cluster.global.mbarrier::complete_tx::bytes [%0], [%1], %2, [%3];"
                 :: "r"(dst), "l"(src), "r"(bytes), "r"(bar) : "memory");
}
__device__ __forceinline__ void l2_prefetch(const void* p, uint32_t bytes) {
    asm volatile("cp.async.bulk.prefetch.L2.global [%0], %1;" :: "l"(p), "r"(bytes) : "memory");
}
__device__ __forceinline__ uint32_t pack_bf16(float lo, float hi) {
    uint32_t r; asm("cvt.rn.bf16x2.f32 %0, %1, %2;" : "=r"(r) : "f"(hi), "f"(lo)); return r;
}
__device__ __forceinline__ float ex2(float x) { float r; asm("ex2.approx.ftz.f32 %0, %1;" : "=f"(r) : "f"(x)); return r; }
__device__ __forceinline__ float rcp(float x) { float r; asm("rcp.approx.ftz.f32 %0, %1;" : "=f"(r) : "f"(x)); return r; }
__device__ __forceinline__ float bf_lo(uint32_t v) { return __uint_as_float(v << 16); }
__device__ __forceinline__ float bf_hi(uint32_t v) { return __uint_as_float(v & 0xFFFF0000u); }
__device__ __forceinline__ float bf_round(float x) { return __bfloat162float(__float2bfloat16_rn(x)); }
__device__ __forceinline__ bool elect_one() {
    uint32_t r; asm volatile("{\n.reg .pred p;\nelect.sync _|p, 0xffffffff;\nselp.u32 %0, 1, 0, p;\n}" : "=r"(r)); return r;
}
__device__ __forceinline__ int warp_uniform(int v) { return __shfl_sync(0xffffffffu, v, 0); }
__device__ __forceinline__ int tok_of(int u) { return 2 * (u & 1023) + (u >> 10); }

#define PFA 7
#define NSKV 200
#define NSS 300
#define NSP 13
#define EV 4
#define PF1 4
#define XRD 2
#define GAT 4
#define MC0 1
constexpr int K1_ST = 4;
constexpr int K1_XB = 10 * 16384, K1_WB = 16384;
constexpr int K1_SMEM = K1_XB + K1_ST * K1_WB + 1024;
constexpr float QSCALE = 0.22360679774997896f * 1.4426950408889634f;

__device__ __forceinline__ void signal(uint32_t* c) { asm volatile("red.release.gpu.global.add.u32 [%0], 1;" :: "l"(c) : "memory"); }
__device__ __forceinline__ void wait_count(const uint32_t* c, uint32_t n, uint32_t ns) {
    uint32_t v;
    #pragma unroll 1
    for (int i = 0; i < (1 << 20); i++) {
        asm volatile("ld.acquire.gpu.global.u32 %0, [%1];" : "=r"(v) : "l"(c) : "memory");
        if (v >= n) break;
        __nanosleep(ns);
    }
    asm volatile("fence.proxy.async.global;" ::: "memory");
}

__device__ __forceinline__ void k1_pack_b(const float (&acc)[120], uint32_t (&pk)[60], int c0) {
    #pragma unroll
    for (int hp = 0; hp < 6; hp++) {
        if (c0 + hp * 40 < 640) {
            #pragma unroll
            for (int i = 0; i < 10; i++) pk[hp * 10 + i] = pack_bf16(acc[hp * 20 + 2 * i] * QSCALE, acc[hp * 20 + 2 * i + 1] * QSCALE);
        } else {
            #pragma unroll
            for (int i = 0; i < 10; i++) pk[hp * 10 + i] = pack_bf16(acc[hp * 20 + 2 * i], acc[hp * 20 + 2 * i + 1]);
        }
    }
}
__device__ __forceinline__ uint32_t hfma2b(uint32_t a, uint32_t b, uint32_t c) { uint32_t r; asm("fma.rn.bf16x2 %0, %1, %2, %3;" : "=r"(r) : "r"(a), "r"(b), "r"(c)); return r; }
__device__ __forceinline__ uint32_t hmul2b(uint32_t a, uint32_t b) { uint32_t r; asm("mul.rn.bf16x2 %0, %1, %2;" : "=r"(r) : "r"(a), "r"(b)); return r; }
__device__ __forceinline__ uint32_t hadd2b(uint32_t a, uint32_t b) { uint32_t r; asm("add.rn.bf16x2 %0, %1, %2;" : "=r"(r) : "r"(a), "r"(b)); return r; }
__device__ __forceinline__ uint32_t hmax2b(uint32_t a, uint32_t b) { uint32_t r; asm("max.NaN.bf16x2 %0, %1, %2;" : "=r"(r) : "r"(a), "r"(b)); return r; }
__device__ __forceinline__ uint32_t norm_part(uint32_t a0, uint32_t a1, uint32_t a2, uint32_t b0, uint32_t b1, uint32_t b2) {
    const uint32_t x = hfma2b(a2, a2, hfma2b(a1, a1, hmul2b(a0, a0))), y = hfma2b(b2, b2, hfma2b(b1, b1, hmul2b(b0, b0)));
    return hadd2b(__byte_perm(x, y, 0x5410), __byte_perm(x, y, 0x7632));
}
__device__ __forceinline__ uint32_t quad_sum(uint32_t s) {
    s = hadd2b(s, __shfl_xor_sync(~0u, s, 1));
    return hadd2b(s, __shfl_xor_sync(~0u, s, 2));
}
__device__ __forceinline__ uint32_t norm2(uint32_t a0, uint32_t a1, uint32_t a2, uint32_t b0, uint32_t b1, uint32_t b2) {
    return quad_sum(norm_part(a0, a1, a2, b0, b1, b2));
}
__device__ __forceinline__ uint32_t pin(uint32_t v, int lane) { return __shfl_sync(~0u, v, lane); }
__device__ __forceinline__ uint8_t* pin(uint8_t* p, int lane) { return (uint8_t*)__shfl_sync(~0u, (unsigned long long)p, lane); }
__device__ __forceinline__ void stg32(uint8_t* p, uint32_t v) { asm volatile("st.global.b32 [%0], %1;" :: "l"(p), "r"(v) : "memory"); }
struct BStore {
    uint8_t* dq; uint8_t* dk;
    uint32_t h0, h1, m0, m1;
};
template<int PIECE>
__device__ __forceinline__ void k1_store_b(const uint32_t* pkb, int ng, int lane, const BStore& b, uint32_t (&np)[12]) {
    constexpr int HS = PIECE >> 1, HF = PIECE & 1, ODD = HS & 1;
    const uint32_t* pk = pkb + (HS >> 1) * 10;
    const int pr = ng * 6 + (HS >> 1);
    const bool dat = ODD ? (lane & 2) != 0 : (lane & 2) == 0;
    const uint32_t* a = pk + ODD * 6;
    if (pr < 16) {
        uint8_t* d = b.dq + (HS >> 1) * (128 * 1280);
        if (!HF) asm volatile("st.global.v4.b32 [%0], {%1,%2,%3,%4};" :: "l"(d + ODD * 512), "r"(a[0]), "r"(a[1]), "r"(a[2]), "r"(a[3]) : "memory");
        else if (ODD) asm volatile("st.global.v2.b32 [%0], {%1,%2};" :: "l"(d + 1024 - lane * 8), "r"(pk[4]), "r"(pk[5]) : "memory");
        if (HF) np[HS] = 0;
        return;
    }
    const uint32_t s = dat ? pk[4 + HF] : 0u;
    if (pr < 32) {
        uint8_t* d = b.dk + HS * (2 * XHEAD) + HF * 384;
        const uint32_t h = HF ? b.h1 : b.h0;
        stg32(d, hmul2b(a[HF], h)); stg32(d + 128, hmul2b(a[2 + HF], h)); stg32(d + 256, hfma2b(s, h, dat ? 0u : HF ? b.m1 : b.m0));
    } else {
        uint8_t* d = b.dk + (HS - 32) * (2 * XHEAD) + 6144 + HF * 384;
        stg32(d, a[HF]); stg32(d + 128, a[2 + HF]); stg32(d + 256, (lane & 3) == (ODD ? 0 : 2) ? 0x00003F80u : s);
    }
    const uint32_t x = hfma2b(s, s, hfma2b(a[2 + HF], a[2 + HF], hmul2b(a[HF], a[HF])));
    np[HS] = HF ? hadd2b(__byte_perm(np[HS], x, 0x5410), __byte_perm(np[HS], x, 0x7632)) : x;
}
template<int P0, int P1> __device__ __forceinline__ void k1_store_range(const uint32_t* pkb, int ng, int lane, const BStore& b, uint32_t (&np)[12]) {
    if constexpr (P0 < P1 && P0 < 24) { k1_store_b<P0>(pkb, ng, lane, b, np); k1_store_range<P0 + 1, P1>(pkb, ng, lane, b, np); }
}
__device__ __forceinline__ uint32_t transp(uint32_t v) { asm volatile("movmatrix.sync.aligned.m8n8.trans.b16 %0, %0;" : "+r"(v)); return v; }
__device__ __forceinline__ void mma16816(float* d, uint32_t a0, uint32_t a1, uint32_t a2, uint32_t a3, uint32_t b0, uint32_t b1) {
    asm("mma.sync.aligned.m16n8k16.row.col.f32.bf16.bf16.f32 {%0,%1,%2,%3}, {%4,%5,%6,%7}, {%8,%9}, {%0,%1,%2,%3};"
                 : "+f"(d[0]), "+f"(d[1]), "+f"(d[2]), "+f"(d[3]) : "r"(a0), "r"(a1), "r"(a2), "r"(a3), "r"(b0), "r"(b1));
}
__device__ __forceinline__ void mma1688(float* d, uint32_t a0, uint32_t a1, uint32_t b0) {
    asm("mma.sync.aligned.m16n8k8.row.col.f32.bf16.bf16.f32 {%0,%1,%2,%3}, {%4,%5}, {%6}, {%0,%1,%2,%3};"
                 : "+f"(d[0]), "+f"(d[1]), "+f"(d[2]), "+f"(d[3]) : "r"(a0), "r"(a1), "r"(b0));
}

struct Win { bool up0, up1; uint32_t msk; };
__device__ __forceinline__ Win make_win(int lane) {
    Win w; w.up0 = 2 * (lane & 3) > (lane >> 2); w.up1 = 2 * (lane & 3) + 1 > (lane >> 2);
    w.msk = (w.up0 ? 0xFFFFu : 0u) | (w.up1 ? 0xFFFF0000u : 0u);
    return w;
}
template<int NP>
__device__ __forceinline__ void local_pairs(uint2 (&r)[NP * 5], const uint2* q, const uint2* k, const uint2* v, const uint32_t* kp, const uint32_t* vp,
                                            const Win& w, bool halo, bool lo) {
    constexpr int NHD = 2 * NP;
    float a[NHD][4], m[NHD][2];
    #pragma unroll
    for (int h = 0; h < NHD; h++) {
        const int c = (h >> 1) * 5 + (h & 1) * 3, sh = (h >> 1) * 5 + 2;
        const bool mine = (h & 1) ? !lo : lo;
        const uint32_t qx = mine ? q[sh].x : 0u, qy = mine ? q[sh].y : 0u;
        float s[12];
        #pragma unroll
        for (int i = 0; i < 12; i++) s[i] = 0.f;
        mma16816(s + 4, q[c].x, q[c].y, q[c + 1].x, q[c + 1].y, k[c].x, k[c + 1].x);   mma1688(s + 4, qx, qy, k[sh].x);
        mma16816(s + 8, q[c].x, q[c].y, q[c + 1].x, q[c + 1].y, k[c].y, k[c + 1].y);   mma1688(s + 8, qx, qy, k[sh].y);
        mma16816(s, q[c].x, q[c].y, q[c + 1].x, q[c + 1].y, kp[c], kp[c + 1]);         mma1688(s, qx, qy, kp[sh]);
        const float ninf = __uint_as_float(0xFF800000u);
        a[h][0] = w.up0 ? (halo ? s[0] : ninf) : s[4]; a[h][1] = w.up1 ? (halo ? s[1] : ninf) : s[5];
        a[h][2] = w.up0 ? s[6] : s[10]; a[h][3] = w.up1 ? s[7] : s[11];
        m[h][0] = fmaxf(a[h][0], a[h][1]); m[h][1] = fmaxf(a[h][2], a[h][3]);
    }
    #pragma unroll
    for (int o = 1; o <= 2; o++)
        #pragma unroll
        for (int h = 0; h < NHD; h++) { m[h][0] = fmaxf(m[h][0], __shfl_xor_sync(~0u, m[h][0], o)); m[h][1] = fmaxf(m[h][1], __shfl_xor_sync(~0u, m[h][1], o)); }
    #pragma unroll
    for (int h = 0; h < NHD; h++) {
        #pragma unroll
        for (int i = 0; i < 4; i++) a[h][i] = ex2((a[h][i] - m[h][i >> 1]) * QSCALE);
        m[h][0] = a[h][0] + a[h][1]; m[h][1] = a[h][2] + a[h][3];
    }
    #pragma unroll
    for (int o = 1; o <= 2; o++)
        #pragma unroll
        for (int h = 0; h < NHD; h++) { m[h][0] += __shfl_xor_sync(~0u, m[h][0], o); m[h][1] += __shfl_xor_sync(~0u, m[h][1], o); }
    #pragma unroll
    for (int pp = 0; pp < NP; pp++) {
        float o[2][12];
        #pragma unroll
        for (int e = 0; e < 2; e++) {
            const int h = 2 * pp + e, c = pp * 5 + e * 3, sh = pp * 5 + 2;
            const float ra = rcp(m[h][0]), rb = rcp(m[h][1]);
            const uint32_t pa = pack_bf16(a[h][0] * ra, a[h][1] * ra), pb = pack_bf16(a[h][2] * rb, a[h][3] * rb);
            const uint32_t p0 = pa & w.msk, p2 = pa & ~w.msk, p3 = pb & w.msk, p5 = pb & ~w.msk;
            #pragma unroll
            for (int i = 0; i < 12; i++) o[e][i] = 0.f;
            mma16816(o[e], p0, 0u, p2, p3, vp[c], v[c].x);              mma1688(o[e], 0u, p5, v[c].y);
            mma16816(o[e] + 4, p0, 0u, p2, p3, vp[c + 1], v[c + 1].x);  mma1688(o[e] + 4, 0u, p5, v[c + 1].y);
            mma16816(o[e] + 8, p0, 0u, p2, p3, vp[sh], v[sh].x);        mma1688(o[e] + 8, 0u, p5, v[sh].y);
            r[c] = make_uint2(pack_bf16(o[e][0], o[e][1]), pack_bf16(o[e][2], o[e][3]));
            r[c + 1] = make_uint2(pack_bf16(o[e][4], o[e][5]), pack_bf16(o[e][6], o[e][7]));
        }
        r[pp * 5 + 2] = make_uint2(pack_bf16(lo ? o[0][8] : o[1][8], lo ? o[0][9] : o[1][9]), pack_bf16(lo ? o[0][10] : o[1][10], lo ? o[0][11] : o[1][11]));
    }
}

__device__ __forceinline__ void retile_wo(const uint8_t* __restrict__ w, uint4* __restrict__ dst, int e, int wid, int nw, int lane) {
    const int cg = lane >> 3;
    #pragma unroll 1
    for (int it = wid; it < 40; it += nw) {
        const int kg = e * 20 + (it >> 1), hf = it & 1;
        const uint4* s = (const uint4*)(w + (kg * 8 + (lane & 7)) * 1280) + hf * 40 + cg;
        uint4* d = dst + hf * 25600 + kg * 80 + (lane & 7);
        uint4 v[10];
        #pragma unroll
        for (int i = 0; i < 10; i++) v[i] = __ldg(s + i * 4);
        #pragma unroll
        for (int i = 0; i < 10; i++) { const int n = i * 4 + cg; d[(n / 10) * 6400 + (n % 10) * 8] = v[i]; }
    }
}

__global__ void __cluster_dims__(2, 1, 1) __launch_bounds__(384, 1)
k1_qkv(const __grid_constant__ CUtensorMap tmx, const __grid_constant__ CUtensorMap tmwb, const __grid_constant__ CUtensorMap tmwa,
       const __grid_constant__ CUtensorMap tmwg, const __grid_constant__ CUtensorMap tmwn, const __nv_bfloat16* __restrict__ x, const __nv_bfloat16* __restrict__ gw,
       const uint8_t* __restrict__ wb, const uint8_t* __restrict__ wa, const uint8_t* __restrict__ woa, uint64_t zero) {
    extern __shared__ uint8_t smem_raw[];
    constexpr int AR = K1_ST + EV;
    __shared__ __align__(8) uint64_t bars[13 + 2 * K1_ST + 2 * AR];
    const uint32_t sx = (smem_u32(smem_raw) + 1023) & ~1023u, sw = sx + K1_XB;
    const uint32_t bx = smem_u32(bars), bdone = bx + 80, bgate = bx + 88, bfull = bx + 104, afull = bfull + 8 * K1_ST,
                   bempty = afull + 8 * AR, aempty = bempty + 8 * K1_ST;
    const int rank = blockIdx.x & 1, mt = blockIdx.x & 15, ng = (blockIdx.x >> 4) & 7;
    const int wid = warp_uniform(threadIdx.x >> 5), lane = threadIdx.x & 31;
    if (blockIdx.x >= 128) {
        asm volatile("griddepcontrol.launch_dependents;" ::: "memory");
        retile_wo(woa, g_Wo, blockIdx.x - 128, wid, 12, lane);
        return;
    }
    auto load_wb = [&](int ks, int st) {
        mbar_expect(bfull + 8 * st, 15360);
        #pragma unroll
        for (int b = 0; b < 4; b++) tma2d(sw + st * K1_WB + b * 4096, b < 3 ? &tmwb : &tmwn, bfull + 8 * st, ng * 240 + b * 64, ks * 32);
    };
    auto load_wb_mc = [&](int ks, int st) {
        mbar_expect(bfull + 8 * st, 15360);
        #pragma unroll
        for (int b = 0; b < 2; b++) tma2d_mc(sw + st * K1_WB + (rank * 2 + b) * 4096, rank * 2 + b < 3 ? &tmwb : &tmwn, bfull + 8 * st, ng * 240 + (rank * 2 + b) * 64, ks * 32);
    };
    auto load_x = [&](int c, int slot) { mbar_expect(bx + 8 * c, 16384); tma2d(sx + slot * 16384, &tmx, bx + 8 * c, (mt >> 3) * 640 + c * 64, (mt & 7) * 128); };
    auto load_wa = [&](int j, int r) {
        const int k0 = (9 - (j >> 1)) * 64 + (j & 1) * 32;
        const uint32_t d = sx + (r < EV ? r : 10 + r - EV) * 16384, b = afull + 8 * r;
        mbar_expect(b, 15360);
        #pragma unroll
        for (int p = 0; p < 3; p++) tma2d(d + p * 4096, &tmwa, b, p * 640 + ng * 80, k0);
        tma2d(d + 12288, &tmwg, b, ng * 64, k0);
    };
    if (wid == 8 && elect_one()) {
        asm volatile("prefetch.tensormap [%0];" :: "l"(&tmx) : "memory");
        asm volatile("prefetch.tensormap [%0];" :: "l"(&tmwb) : "memory");
        asm volatile("prefetch.tensormap [%0];" :: "l"(&tmwn) : "memory");
        mbar_init(bx, 1); mbar_init(bfull, 1);
        asm volatile("fence.mbarrier_init.release.cluster;" ::: "memory");
        load_x(0, 0); load_wb(0, 0);
        #pragma unroll
        for (int i = 1; i < 13 + 2 * K1_ST + 2 * AR; i++) if (i != 13) mbar_init(bx + 8 * i, i == 10 ? 9 : i == 11 ? 2 : i >= 13 + 2 * K1_ST + AR ? 2 : i >= 13 + K1_ST + AR ? 4 : 1);
        asm volatile("fence.mbarrier_init.release.cluster;" ::: "memory");
        if (MC0 > 1) load_wb(1, 1);
        load_x(1, 1);
        if (MC0 > 2) load_wb(2, 2);
        if (MC0 > 3) load_wb(3, 3);
    }
    if (threadIdx.x == 0) TS(0, 0);
    __syncwarp();
    asm volatile("barrier.cluster.arrive.relaxed.aligned;" ::: "memory");
    if (wid == 8 && MC0 < 4) {
        asm volatile("barrier.cluster.wait.aligned;" ::: "memory");
        if (elect_one()) {
            #pragma unroll
            for (int i = MC0; i < 4; i++) load_wb_mc(i, i);
        }
    }
    __syncthreads();
    if (wid >= 8) {
        asm volatile("setmaxnreg.dec.sync.aligned.u32 40;");
        if (wid == 8) {
            if (elect_one()) {
                asm volatile("prefetch.tensormap [%0];" :: "l"(&tmwa) : "memory");
                asm volatile("prefetch.tensormap [%0];" :: "l"(&tmwg) : "memory");
                load_x(2, 2); load_x(3, 3);
                #pragma unroll 1
                for (int ks = K1_ST; ks < 20; ks++) {
                    mbar_wait(bempty + 8 * (ks % K1_ST), (ks / K1_ST - 1) & 1);
                    load_wb_mc(ks, ks % K1_ST);
                    if (ks < 10) load_x(ks, ks);
                }
                mbar_wait(bgate, 0);
                asm volatile("fence.proxy.async.global;" ::: "memory");
                int r = 0, ph = 1;
                #pragma unroll 1
                for (int j = 0; j < 20; j++) {
                    if (j >= AR) mbar_wait(aempty + 8 * r, ph); else if (j >= EV) mbar_wait(bempty + 8 * (j - EV), 0);
                    load_wa(j, r);
                    const int i = j - AR - 1 - XRD;
                    if (i >= 0 && !(i & 1) && i / 2 < EV) { mbar_wait(bgate + 8, 0); load_x(EV - 1 - i / 2, 9 - i / 2); }
                    if (++r == AR) { r = 0; ph ^= 1; }
                }
            }
        } else {
            if (wid == 9) {
                if (lane == 16) l2_prefetch(wb + 128 * 3840 + (size_t)blockIdx.x * 15360, 15360);
                if (lane < 16) l2_prefetch(x + (size_t)tok_of(mt * 128 + ng * 16 + lane) * DM + 256, 768);
                if (blockIdx.x < 18) g_cnt[blockIdx.x][lane] = 0;
                float s[4] = {0.f, 0.f, 0.f, 0.f};
                const int j = lane & 7, r0 = lane >> 3;
                if (lane < 10) asm volatile("prefetch.global.L1 [%0];" :: "l"(gw + lane * 64));
                #pragma unroll 1
                for (int c = 0; c < 10; c++) {
                    if (c == EV) { __syncwarp(); if (lane == 0) mbar_arrive(bgate); }
                    const uint4 w = __ldg((const uint4*)gw + c * 8 + j);
                    mbar_wait_ns<NSS>(bx + 8 * c, 0);
                    #pragma unroll
                    for (int i = 0; i < 4; i++) {
                        const int r = ng * 16 + i * 4 + r0;
                        uint4 v;
                        asm volatile("ld.shared.v4.b32 {%0,%1,%2,%3}, [%4];" : "=r"(v.x), "=r"(v.y), "=r"(v.z), "=r"(v.w)
                                     : "r"(sx + c * 16384 + r * 128 + ((j ^ (r & 7)) << 4)));
                        const uint32_t p0 = hmul2b(v.x, w.x), p1 = hmul2b(v.y, w.y), p2 = hmul2b(v.z, w.z), p3 = hmul2b(v.w, w.w);
                        s[i] += ((bf_lo(p0) + bf_hi(p0)) + (bf_lo(p1) + bf_hi(p1))) + ((bf_lo(p2) + bf_hi(p2)) + (bf_lo(p3) + bf_hi(p3)));
                    }
                }
                __syncwarp();
                if (lane == 0) mbar_arrive(bgate + 8);
                #pragma unroll
                for (int i = 0; i < 4; i++) {
                    s[i] += __shfl_xor_sync(~0u, s[i], 1); s[i] += __shfl_xor_sync(~0u, s[i], 2); s[i] += __shfl_xor_sync(~0u, s[i], 4);
                }
                if (j < 4) {
                    const float z = j == 0 ? s[0] : j == 1 ? s[1] : j == 2 ? s[2] : s[3];
                    const float g = bf_round(1.f / (1.f + __expf(-bf_round(z))));
                    g_gate[mt * 128 + ng * 16 + j * 4 + r0] = make_float2(g, bf_round(1.f - g));
                }
                __syncwarp();
                if (lane == 0) {
                    mbar_arrive(bdone);
                    mbar_wait_ns<64>(bdone, 0);
                    __threadfence();
                    asm volatile("griddepcontrol.launch_dependents;" ::: "memory");
                }
            } else if (wid == 11) {
                mbar_wait_ns<NSS>(bx + 8 * GAT, 0);
                if ((lane & 7) < 6) {
                    const uint4* s = (const uint4*)(wa + blockIdx.x * (5 * 3840) + ((lane & 7) >> 1) * 1280 + (lane >> 3) * 160 + 128) + (lane & 1);
                    uint4* d = g_Wg + blockIdx.x * (5 * 64) + lane;
                    #pragma unroll
                    for (int h = 0; h < 2; h++) {
                        uint4 v[5];
                        #pragma unroll
                        for (int i = 0; i < 5; i++) v[i] = __ldcg(s + i * 240 + h * 40);
                        #pragma unroll
                        for (int i = 0; i < 5; i++) d[i * 64 + h * 32] = v[i];
                    }
                }
                __syncwarp();
                if (lane == 0) { signal(&g_gcnt); wait_count(&g_gcnt, 128, 200); mbar_arrive(bgate); }
            } else if (wid == 10) {
                mbar_wait_ns<NSS>(bx + 8 * PF1, 0);
                if (lane == 0) l2_prefetch(wa + (size_t)(512 + blockIdx.x) * 3840, 3840);
                mbar_wait_ns<NSS>(bx + 8 * PFA, 0);
                if (lane == 0) l2_prefetch(wa + (size_t)blockIdx.x * 15360, 15360);
            }
        }
    } else {
        asm volatile("setmaxnreg.inc.sync.aligned.u32 232;");
        asm volatile("barrier.cluster.wait.aligned;" ::: "memory");
        const int wg = wid >> 2;
        const int ug = mt * 16 + wid * 2;
        const bool sig = (threadIdx.x & 127) == 0, sig2 = (threadIdx.x & 95) == 0;
        uint32_t brel;
        asm("mapa.shared::cluster.u32 %0, %1, %2;" : "=r"(brel) : "r"(bempty), "r"(wid & 1));
        uint64_t da0 = mkdesc(sx + wg * 8192, 16, 1024, 1) + zero;
        uint32_t pkb[60];
        BStore bs;
        bs.dq = pin(g_XB + ng * 6 * (128 * 1280) + (ug >> 1) * 1280 + lane * 16, lane);
        bs.dk = pin(g_XB + XPART + (ng * 12 - 32) * (2 * XHEAD) + mt * 12288 + wid * 768 + lane * 4, lane);
        {
            const bool y0 = (POLY_PAT >> (ug & 31)) & 1, y1 = (POLY_PAT >> ((ug & 31) + 1)) & 1;
            const uint32_t mg = (lane & 1) ? 0x00003AACu : 0x3F33433Eu;
            bs.h0 = pin(y0 ? 0x3F003F00u : 0x3F803F80u, lane); bs.h1 = pin(y1 ? 0x3F003F00u : 0x3F803F80u, lane);
            bs.m0 = pin(y0 ? mg : 0u, lane); bs.m1 = pin(y1 ? mg : 0u, lane);
        }
        uint32_t np[12], nk = 0, nv = 0;
        const uint64_t db0 = mkdesc(sw, 4096, 1024, 1);
        {
            float acc[120];
            #pragma unroll
            for (int i = 0; i < 120; i++) acc[i] = 0.f;
            fence_regs(acc);
            #pragma unroll 1
            for (int r = 0; r < 5; r++) {
                #pragma unroll
                for (int st = 0; st < K1_ST; st++) {
                    if (!(st & 1)) mbar_wait(bx + 16 * r + 4 * st, 0);
                    mbar_wait(bfull + 8 * st, r & 1);
                    if (threadIdx.x == 0 && ((r == 0 && st == 0) || (r == 2 && st == 2))) TS(0, 1 + (r ? 1 : 0));
                    const uint64_t da = da0 + (r * 2048 + (st >> 1) * 1024 + (st & 1) * 4), db = db0 + st * (K1_WB >> 4);
                    wg_fence();
                    wgmma_ss_n240<0, 1>(acc, da, db, 1);
                    wgmma_ss_n240<0, 1>(acc, da + 2, db + 128, 1);
                    wg_commit();
                    wg_wait<1>();
                    if ((st > 0 || r > 0) && sig2) mbar_arrive_cluster((r < 4 || st == 0 ? brel : bempty) + 8 * ((st + K1_ST - 1) % K1_ST));
                }
            }
            wg_wait<0>();
            fence_regs(acc);
            if (sig2) mbar_arrive(bempty + 8 * (19 % K1_ST));
            if (threadIdx.x == 0) TS(0, 3);
            k1_pack_b(acc, pkb, ng * 240);
        }
        uint2 q[10], k[10], v[10];
        {
            float acc[120];
            uint64_t dw0 = mkdesc(sx, 4096, 1024, 1);
            #pragma unroll
            for (int kk = 0; kk < 20; kk++) {
                const int r = kk % AR, ws = r < EV ? r : 10 + r - EV, c = 9 - (kk >> 1), xs = c < EV ? 10 - EV + c : c;
                if (r == 0) { da0 += zero; dw0 += zero; }
                if (c < EV && !(kk & 1)) mbar_wait(bx + 8 * c, 1);
                mbar_wait(afull + 8 * r, (kk / AR) & 1);
                if (threadIdx.x == 0 && (kk == 0 || kk == 10)) TS(0, 4 + (kk ? 1 : 0));
                const uint64_t da = da0 + (xs * 1024 + (kk & 1) * 4), db = dw0 + ws * 1024;
                wg_fence();
                if (kk == 0) wgmma_ss_n240_z<0, 1>(acc, da, db); else wgmma_ss_n240<0, 1>(acc, da, db, 1);
                wgmma_ss_n240<0, 1>(acc, da + 2, db + 128, 1);
                wg_commit();
                wg_wait<1>();
                if (kk > 0 && kk <= 20 - AR && sig) mbar_arrive(aempty + 8 * ((kk - 1) % AR));
                switch (kk) {
#define SB(K) case K: k1_store_range<(K * 24 + NSP - 1) / NSP, ((K + 1) * 24 + NSP - 1) / NSP>(pkb, ng, lane, bs, np); break;
                    SB(0) SB(1) SB(2) SB(3) SB(4) SB(5) SB(6) SB(7) SB(8) SB(9) SB(10) SB(11) SB(12) SB(13) SB(14) SB(15) SB(16) SB(17) SB(18)
#undef SB
                    default: break;
                }
                if ((kk == NSP / 2 + 1 || kk == NSP) && ng >= 2) {
                    #pragma unroll
                    for (int i = kk == NSP ? 6 : 0; i < (kk == NSP ? 12 : 6); i += 2) {
                        const uint32_t m = hmax2b(quad_sum(np[i]), quad_sum(np[i + 1]));
                        if (ng * 6 + (i >> 1) < 32) nk = hmax2b(nk, m); else nv = hmax2b(nv, m);
                    }
                }
                if (kk == NSP) {
                    const uint32_t a = __reduce_max_sync(~0u, max(nk << 16, nk & 0xFFFF0000u));
                    const uint32_t b = __reduce_max_sync(~0u, max(nv << 16, nv & 0xFFFF0000u));
                    if (lane == 0) {
                        g_nmax[0][ng][mt * 8 + wid] = __uint_as_float(a); g_nmax[1][ng][mt * 8 + wid] = __uint_as_float(b);
                    }
                    __syncwarp();
                    if (lane == 0) mbar_arrive(bdone);
                }
            }
            wg_wait<0>();
            fence_regs(acc);
            if (threadIdx.x == 0) TS(0, 6);
            #pragma unroll
            for (int j = 0; j < 10; j++) {
                const float* a = j < 8 ? &acc[4 * (8 + j)] : &acc[4 * (18 + j)];
                k[j] = make_uint2(pack_bf16(a[0], a[1]), pack_bf16(a[2], a[3]));
                a = j < 8 ? &acc[4 * (16 + j)] : &acc[4 * (20 + j)];
                v[j] = make_uint2(transp(pack_bf16(a[0], a[1])), transp(pack_bf16(a[2], a[3])));
                a = j < 8 ? &acc[4 * j] : &acc[4 * (16 + j)];
                q[j] = make_uint2(pack_bf16(a[0], a[1]), pack_bf16(a[2], a[3]));
            }
        }
        uint32_t kp[10], vp[10];
        {
            const uint32_t ex = sx + 4 * 16384 + wid * 2048 + lane * 16;
            #pragma unroll
            for (int j = 0; j < 5; j++)
                asm volatile("st.shared.v4.b32 [%0], {%1,%2,%3,%4};" :: "r"(ex + (j & 3) * 512 + (j >> 2) * 16384),
                             "r"(k[2 * j].y), "r"(k[2 * j + 1].y), "r"(v[2 * j].y), "r"(v[2 * j + 1].y) : "memory");
            if (wg == 0) {
                asm volatile("barrier.cta.arrive.aligned 2, 256;" ::: "memory");
                asm volatile("barrier.cta.sync.aligned 1, 128;" ::: "memory");
            } else asm volatile("barrier.cta.sync.aligned 2, 256;" ::: "memory");
            #pragma unroll
            for (int j = 0; j < 10; j++) { kp[j] = 0; vp[j] = 0; }
            if (wid > 0) {
                #pragma unroll
                for (int j = 0; j < 5; j++)
                    asm volatile("ld.shared.v4.b32 {%0,%1,%2,%3}, [%4];" : "=r"(kp[2 * j]), "=r"(kp[2 * j + 1]), "=r"(vp[2 * j]), "=r"(vp[2 * j + 1])
                                 : "r"(ex - 2048 + (j & 3) * 512 + (j >> 2) * 16384) : "memory");
            }
            uint32_t* hb = g_HB + (mt * 16 + ng * 2) * 800 + lane;
            if (wid == 0) {
                #pragma unroll
                for (int j = 0; j < 10; j++) { uint32_t* d = hb + (j / 5) * 800 + (j % 5) * 32; d[0] = q[j].x; d[160] = k[j].x; d[320] = v[j].x; }
            }
            if (wid == 7) {
                #pragma unroll
                for (int j = 0; j < 10; j++) { uint32_t* d = hb + (j / 5) * 800 + (j % 5) * 32; d[480] = k[j].y; d[640] = v[j].y; }
            }
        }
        if (threadIdx.x == 0) TS(0, 7);
        const Win win = make_win(lane);
        const bool keep = wid > 0 || (mt & 7) == 0;
        uint32_t* dst = g_O + ((ug >> 3) * 80 + ng * 10) * 256 + (ug & 7) * 32 + lane;
        uint2 r[10];
        local_pairs<2>(r, q, k, v, kp, vp, win, wid > 0, (lane & 3) < 2);
        #pragma unroll
        for (int c = 0; c < 10; c++) { if (keep) dst[c * 256] = r[c].x; dst[c * 256 + 32] = r[c].y; }
        if (threadIdx.x == 0) TS(0, 8);
        if (threadIdx.x == 224) TS(0, 9);
    }
}

#define VOFF 256
#define VT(t) ((t) >= VOFF ? (t) - VOFF : (t) + 512)
#define SLOWNS 150
#define GRP 2
template<int V> struct Int { static constexpr int value = V; };
constexpr int K2_ST = 4;
constexpr int KV_STAGE = 12288;
constexpr int K2_WOB = K2_ST * KV_STAGE, K2_STR = K2_WOB + 102400;
constexpr int SR_ST = 3, SR_SLOT = 18432;
constexpr int K2_SMEM = K2_STR + SR_ST * SR_SLOT + 1024;
constexpr int B_KVF = 0, B_KVE = 32, B_O = 64, B_D = 96, B_SF = 104, B_SE = 128, B_X = 152, B_W = 216, B_T = 224, B_L = 232, B_Q = 240, B_G = 248, B_R = 256, B_H = 264, B_P = 328, B_NUM = 42;

__device__ __forceinline__ uint32_t exp_mufu(float a, float b) { return pack_bf16(ex2(a), ex2(b)); }
__device__ __forceinline__ uint32_t exp_poly(float a, float b, uint32_t c1) {
    uint32_t y, u, w;
    asm("prmt.b32 %0, %2, %1, 0x2165;" : "=r"(y) : "r"(__float_as_uint(a)), "r"(__float_as_uint(b)));
    asm("lop3.b32 %0, %1, %2, 0x007F007F, 0xE4;" : "=r"(u) : "r"(y), "r"(c1));
    asm("fma.rn.bf16x2 %0, %1, %1, %2;" : "=r"(w) : "r"(u), "r"(0x40034003u));
    return w + y - u;
}
template<int B0, int BA, int BB> __device__ __forceinline__ void exp_tile(const float (&s)[32], uint32_t (&p)[16], uint32_t c1) {
    #pragma unroll
    for (int b = BA; b < BB; b++) {
        p[b * 2 + 0] = is_poly(b + B0) ? exp_poly(s[b * 4 + 0], s[b * 4 + 1], c1) : exp_mufu(s[b * 4 + 0], s[b * 4 + 1]);
        p[b * 2 + 1] = is_poly(b + B0) ? exp_poly(s[b * 4 + 2], s[b * 4 + 3], c1) : exp_mufu(s[b * 4 + 2], s[b * 4 + 3]);
    }
}
__device__ __forceinline__ void exp_step_max(float (&s)[16], uint32_t (&p)[8], float (&o)[12], float& m0, float& m1, uint32_t pat) {
    float a0 = m0, a1 = m1;
    #pragma unroll
    for (int b = 0; b < 4; b++) {
        const float f = ((pat >> b) & 1) ? 2.f : 1.f;
        s[b * 4] *= f; s[b * 4 + 1] *= f; s[b * 4 + 2] *= f; s[b * 4 + 3] *= f;
        a0 = fmaxf(a0, fmaxf(s[b * 4], s[b * 4 + 1])); a1 = fmaxf(a1, fmaxf(s[b * 4 + 2], s[b * 4 + 3]));
    }
    a0 = fmaxf(a0, __shfl_xor_sync(~0u, a0, 1)); a1 = fmaxf(a1, __shfl_xor_sync(~0u, a1, 1));
    a0 = fmaxf(a0, __shfl_xor_sync(~0u, a0, 2)); a1 = fmaxf(a1, __shfl_xor_sync(~0u, a1, 2));
    const float r0 = ex2(m0 - a0), r1 = ex2(m1 - a1);
    m0 = a0; m1 = a1;
    #pragma unroll
    for (int j = 0; j < 3; j++) { o[j * 4] *= r0; o[j * 4 + 1] *= r0; o[j * 4 + 2] *= r1; o[j * 4 + 3] *= r1; }
    #pragma unroll
    for (int b = 0; b < 4; b++) {
        p[b * 2 + 0] = exp_mufu(s[b * 4 + 0] - a0, s[b * 4 + 1] - a0);
        p[b * 2 + 1] = exp_mufu(s[b * 4 + 2] - a1, s[b * 4 + 3] - a1);
    }
}
template<int K0, int K1> __device__ __forceinline__ void pvk(float (&o)[12], const uint32_t (&p)[16], uint64_t dv) {
    #pragma unroll
    for (int k = K0; k < K1; k++) wgmma_rs_n24<1>(o, p[k * 4], p[k * 4 + 1], p[k * 4 + 2], p[k * 4 + 3], dv + k * 48, 1);
}
__device__ __forceinline__ void store_o(const float* o, int head, int u0, int lane, float i0, float i1) {
    const int odd = head & 1;
    uint32_t* d = g_O + (32 * 80 + (u0 >> 6) * 80 + (head >> 1) * 5) * 256 + ((u0 >> 3) & 7) * 32 + lane;
    uint32_t* e = d + (odd ? 768 : 0);
    auto st = [](uint32_t* p, uint32_t v) { asm volatile("st.relaxed.gpu.global.b32 [%0], %1;" :: "l"(p), "r"(v) : "memory"); };
    st(e, transp(pack_bf16(o[0] * i0, o[1] * i0)));       st(e + 32, transp(pack_bf16(o[2] * i1, o[3] * i1)));
    st(e + 256, transp(pack_bf16(o[4] * i0, o[5] * i0))); st(e + 288, transp(pack_bf16(o[6] * i1, o[7] * i1)));
    const uint32_t a = transp(pack_bf16(o[8] * i0, o[9] * i0)), b = transp(pack_bf16(o[10] * i1, o[11] * i1));
    if ((lane >= 16) == odd) { st(d + 512, a); st(d + 544, b); }
}
template<int B0>
__device__ __forceinline__ void attn_head(float (&s)[32], uint32_t (&p)[16], float (&o)[12], uint32_t c1, uint64_t dv) {
    wg_wait<0>();
    fence_regs(s);
    exp_tile<B0, 0, 8>(s, p, c1);
}
__device__ __forceinline__ void attn_tail(float (&s)[32], uint32_t (&p)[16], float (&o)[12], const uint32_t (&q)[8], uint64_t dv, uint64_t dk0, uint64_t dk1, bool more = true) {
    wg_fence();
    pvk<0, 4>(o, p, dv);
    if (more) {
        wgmma_rs_n64_z<0>(s, q[0], q[1], q[2], q[3], dk0);
        wgmma_rs_n64<0>(s, q[4], q[5], q[6], q[7], dk1, 1);
    }
    wg_commit();
}
__device__ __forceinline__ void mbar_arrive_if(uint32_t a, uint32_t pred) {
    asm volatile("{\n.reg .pred p;\nsetp.ne.u32 p, %1, 0;\n@p mbarrier.arrive.shared::cta.b64 _, [%0];\n}" :: "r"(a), "r"(pred) : "memory");
}
template<int ST>
__device__ __forceinline__ void attn_tile(float (&s)[32], uint32_t (&p)[16], float (&o)[12], const uint32_t (&q)[8], uint32_t c1,
                                          uint64_t dk0, uint64_t dk1, uint64_t dv0, uint32_t bar, uint32_t rel, uint32_t ph, bool more = true) {
    constexpr uint32_t so = ST * (KV_STAGE >> 4), sn = ((ST + 1) % K2_ST) * (KV_STAGE >> 4);
    attn_head<(ST & 1) * 16>(s, p, o, c1, dv0 + so);
    attn_tail(s, p, o, q, dv0 + so, dk0 + (so + 192), dk1 + (so + 192));
    mbar_arrive_if(bar + B_KVE + 8 * ((ST + K2_ST - 1) % K2_ST), rel);
    if (ST < K2_ST - 1 || ph < 2) mbar_wait(bar + B_KVF + 8 * ((ST + 1) % K2_ST), ph);
    attn_head<(ST & 1) * 16 + 8>(s, p, o, c1, dv0 + (so + 192));
    attn_tail(s, p, o, q, dv0 + (so + 192), dk0 + sn, dk1 + sn, more);
}

__global__ void __launch_bounds__(768, 1)
k2_attn(__nv_bfloat16* __restrict__ out, const uint8_t* __restrict__ wob, uint64_t zero) {
    extern __shared__ uint8_t smem_raw[];
    __shared__ __align__(8) uint64_t bars[B_NUM];
    __shared__ float2 s_lim;
    __shared__ uint4 qpark[2][512];
    __shared__ float gpark[512];
    const int h = blockIdx.x >> 2, qq = blockIdx.x & 3;
    const int wid = warp_uniform(VT(threadIdx.x) >> 5), lane = threadIdx.x & 31;
    const uint32_t skv = (smem_u32(smem_raw) + 1023) & ~1023u, bar = smem_u32(bars);
    const int ns = blockIdx.x & 7, rb0 = ((blockIdx.x >> 5) << 3) + ((blockIdx.x >> 3) & 3);
    if (blockIdx.x >= 128) {
        retile_wo(wob, g_Wo + 51200, blockIdx.x - 128, wid, 24, lane);
        __syncthreads();
        if (threadIdx.x == 0) signal(&g_cnt[0][31]);
        return;
    }
    const uint8_t* KV = g_XB + XPART + (size_t)h * (2 * XHEAD);
    if (wid == 20 && elect_one()) {
        mbar_init(bar + B_KVF, 1);
        asm volatile("fence.mbarrier_init.release.cluster;" ::: "memory");
        asm volatile("fence.proxy.async.global;" ::: "memory");
        mbar_expect(bar + B_KVF, KV_STAGE);
        bulk_g2s(skv, KV, KV_STAGE, bar + B_KVF);
        #pragma unroll
        for (int i = 1; i < B_NUM; i++) mbar_init(bar + 8 * i, 8 * i == B_D ? 16 : (8 * i >= B_KVE && 8 * i < B_D) || (8 * i >= B_X && 8 * i < B_W) ? 4 : 1);
        asm volatile("fence.mbarrier_init.release.cluster;" ::: "memory");
    }
    if (wid >= 20) {
        asm volatile("setmaxnreg.dec.sync.aligned.u32 24;");
        if (wid != 23) __syncthreads();
        else {
            uint4 nk, nv;
            asm volatile("ld.global.cg.v4.b32 {%0,%1,%2,%3}, [%4];" : "=r"(nk.x), "=r"(nk.y), "=r"(nk.z), "=r"(nk.w) : "l"((const uint4*)g_nmax[0][(640 + h * 20) / 240] + lane) : "memory");
            asm volatile("ld.global.cg.v4.b32 {%0,%1,%2,%3}, [%4];" : "=r"(nv.x), "=r"(nv.y), "=r"(nv.z), "=r"(nv.w) : "l"((const uint4*)g_nmax[1][(1280 + h * 20) / 240] + lane) : "memory");
            __syncthreads();
            const float kmax = __uint_as_float(__reduce_max_sync(~0u, max(max(nk.x, nk.y), max(nk.z, nk.w))));
            const float vmax = __uint_as_float(__reduce_max_sync(~0u, max(max(nv.x, nv.y), max(nv.z, nv.w))));
            const float lv = 0.5f * __log2f(vmax);
            const float lim = fminf(100.f, fminf(110.f - lv, 94.f + lv));
            if (lane == 0) {
                const float ql = lim > 0.f && vmax == vmax && kmax < 1e30f ? __fdividef(lim * lim, fmaxf(kmax, 1e-30f) * 1.08f) : -1.f;
                s_lim = make_float2(__uint_as_float(0x3F803F80u), ql);
                mbar_arrive(bar + B_L);
            }
        }
        if (wid == 20) {
            if (elect_one()) {
                #pragma unroll
                for (int i = 1; i < K2_ST; i++) {
                    mbar_expect(bar + B_KVF + 8 * i, KV_STAGE);
                    bulk_g2s(skv + i * KV_STAGE, KV + i * KV_STAGE, KV_STAGE, bar + B_KVF + 8 * i);
                }
                #pragma unroll 1
                for (int r = 1; r < 8; r++) {
                    #pragma unroll
                    for (int st = 0; st < K2_ST; st++) {
                        mbar_wait_ns<NSKV>(bar + B_KVE + 8 * st, (r - 1) & 1);
                        if (st == 0 && (r & 3) == 1) mbar_arrive(bar + (r == 1 ? B_Q : B_P));
                        mbar_expect(bar + B_KVF + 8 * st, KV_STAGE);
                        bulk_g2s(skv + st * KV_STAGE, KV + ((r & 3) * K2_ST + st) * KV_STAGE, KV_STAGE, bar + B_KVF + 8 * st);
                    }
                }
                mbar_arrive(bar + B_T);
            }
        } else if (wid == 21) {
            asm volatile("griddepcontrol.wait;" ::: "memory");
            asm volatile("fence.proxy.async.global;" ::: "memory");
            if (blockIdx.x == 0 && lane == 0) g_gcnt = 0;
            const uint8_t* oa = (const uint8_t*)(g_O + rb0 * 80 * 256);
            if (elect_one()) {
                const uint8_t* w = (const uint8_t*)(g_Wo + ns * 6400);
                mbar_expect(bar + B_W, 102400);
                #pragma unroll
                for (int c = 0; c < 25; c++) {
                    const int sl = c % SR_ST;
                    const uint32_t d = skv + K2_STR + sl * SR_SLOT, b = bar + B_SF + 8 * sl;
                    if ((c == 0 || c == 15) && !(rb0 & 1)) wait_count(&g_cnt[0][(rb0 >> 1) + (c ? 2 : 0)], 16, 500);
                    if (c == 10) {
                        wait_count(&g_cnt[0][31], 4, 500);
                        mbar_wait_ns<NSS>(bar + B_Q, 0);
                        #pragma unroll 1
                        for (int i = 0; i < 5; i++) { bulk_g2s(skv + K2_WOB + i * 20480, w + 8 * 102400 + i * 20480, 20480, bar + B_W); __nanosleep(100); }
                        wait_count(&g_cnt[1][rb0], 32, 500);
                    }
                    if (c >= SR_ST) mbar_wait_ns<NSS>(bar + B_SE + 8 * sl, (c / SR_ST + 1) & 1);
                    if (c < 10 || c >= 15) {
                        const int cc = c < 10 ? c : c - 15;
                        mbar_expect(b, 18432);
                        bulk_g2s(d, oa + (c < 10 ? 0 : 4 * 81920) + cc * 8192, 8192, b); bulk_g2s(d + 8192, w + cc * 10240, 10240, b);
                    } else {
                        mbar_expect(b, 16384);
                        bulk_g2s(d, oa + 32 * 81920 + (c - 10) * 16384, 16384, b);
                    }
                }
            }
            __syncwarp();
            mbar_wait_ns<NSS>(bar + B_R, 0);
            mbar_wait_ns<NSS>(bar + B_T, 0);
            const uint32_t* cnt = &g_cnt[2 + (blockIdx.x >> 3)][lane & 7];
            bool todo = lane < 8;
            #pragma unroll 1
            for (int it = 0; it < (1 << 20); it++) {
                uint32_t v, own;
                asm volatile("ld.relaxed.gpu.global.u32 %0, [%1];" : "=r"(v) : "l"(cnt) : "memory");
                asm volatile("{\n.reg .pred p;\nmbarrier.test_wait.parity.shared::cta.b64 p, [%1], 0;\nselp.u32 %0, 1, 0, p;\n}" : "=r"(own) : "r"(bar + B_D) : "memory");
                if (todo && v >= 4 && (lane < 5 || own)) {
                    mbar_expect(bar + B_H + 8 * lane, 10240);
                    bulk_g2s(skv + (lane < 5 ? K2_STR + lane * 10240 : KV_STAGE + (lane - 5) * 10240), oa + 36 * 81920 + lane * 10240, 10240, bar + B_H + 8 * lane);
                    todo = false;
                }
                if (!__any_sync(~0u, todo)) break;
                if (!own) __nanosleep(SLOWNS);
            }
            if (lane == 0) TSB(8);
        } else if (wid == 22) {
            #pragma unroll 4
            for (int i = 0; i < 16; i++) gpark[i * 32 + lane] = __ldcg(&g_gate[qq * 512 + i * 32 + lane].y);
            mbar_wait_ns<NSS>(bar + B_Q, 0);
            #pragma unroll 1
            for (int w = 0; w < 4; w++) {
                uint8_t* d = (uint8_t*)(g_O + ((36 + qq * 8 + w) * 80 + (h >> 1) * 5) * 256);
                #pragma unroll
                for (int i = 0; i < 5; i++)
                    asm volatile("st.global.v4.b32 [%0], {%1,%1,%1,%1};" :: "l"(i < 4 ? d + (h & 1) * 3072 + i * 512 + lane * 16
                                 : d + 2048 + (lane >> 2) * 128 + (h & 1) * 64 + (lane & 3) * 16), "r"(~0u) : "memory");
            }
            __syncwarp();
            if (elect_one()) mbar_arrive(bar + B_G);
            __syncwarp();
            if (elect_one()) {
                for (int w = 0; w < 4; w++) mbar_wait_ns<NSS>(bar + B_O + 8 * w, 0);
                asm volatile("fence.release.gpu;" ::: "memory");
                for (int w = 0; w < 4; w++) asm volatile("red.relaxed.gpu.global.add.u32 [%0], 1;" :: "l"(&g_cnt[1][qq * 8 + w]) : "memory");
            }
        }
        return;
    }
    if (wid >= 16) {
        TSA(1, 0);
        asm volatile("setmaxnreg.dec.sync.aligned.u32 72;");
        __syncthreads();
        asm volatile("griddepcontrol.wait;" ::: "memory");
        if (wid < 18) {
            const int id = blockIdx.x * 2 + wid - 16, mt = id >> 4, hp = id & 15;
            if (mt & 7) {
                const uint32_t* hb = g_HB + id * 800 + lane;
                uint2 q[5], k[5], v[5], r[5];
                uint32_t kp[5], vp[5];
                #pragma unroll
                for (int c = 0; c < 5; c++) {
                    q[c] = make_uint2(__ldcg(hb + c * 32), 0u); k[c] = make_uint2(__ldcg(hb + 160 + c * 32), 0u); v[c] = make_uint2(__ldcg(hb + 320 + c * 32), 0u);
                    kp[c] = __ldcg(hb - 16 * 800 + 480 + c * 32); vp[c] = __ldcg(hb - 16 * 800 + 640 + c * 32);
                }
                local_pairs<1>(r, q, k, v, kp, vp, make_win(lane), true, (lane & 3) < 2);
                #pragma unroll
                for (int c = 0; c < 5; c++) g_O[(mt * 160 + hp * 5 + c) * 256 + lane] = r[c].x;
            }
            __syncwarp();
            if (elect_one()) signal(&g_cnt[0][mt]);
            __syncwarp();
        }
        uint64_t dA = mkdesc(skv + K2_STR, 1024, 128, 0), dWa = mkdesc(skv + K2_STR + 8192, 1280, 128, 0), dWb = mkdesc(skv + K2_WOB, 1280, 128, 0);
        const uint32_t rel = VT(threadIdx.x) == 512;
        const uint32_t la = skv + K2_STR + (lane >> 4) * 1024 + (wid - 16) * 256 + (lane & 15) * 16;
        #pragma unroll
        for (int job = 0; job < 2; job++) {
            float acc[40];
            const int u = (rb0 + job * 4) * 64 + (wid - 16) * 16 + (lane >> 2);
            const float ga = __ldcg(&g_gate[u].x), gb = __ldcg(&g_gate[u + 8].x);
            auto item = [&](auto tr, int c, int nk, uint64_t w, bool first) {
                constexpr int TR = decltype(tr)::value;
                const int sl = c % SR_ST;
                mbar_wait_ns<NSS>(bar + B_SF + 8 * sl, (c / SR_ST) & 1);
                #pragma unroll
                for (int k = 0; k < nk; k++) {
                    if (k % GRP == 0) {
                        uint32_t f[4];
                        if (TR) asm volatile("ldmatrix.sync.aligned.m8n8.x4.trans.shared.b16 {%0,%1,%2,%3}, [%4];" : "=r"(f[0]), "=r"(f[1]), "=r"(f[2]), "=r"(f[3]) : "r"(la + sl * SR_SLOT + k * 2048) : "memory");
                        else asm volatile("ldmatrix.sync.aligned.m8n8.x4.shared.b16 {%0,%1,%2,%3}, [%4];" : "=r"(f[0]), "=r"(f[1]), "=r"(f[2]), "=r"(f[3]) : "r"(la + sl * SR_SLOT + k * 2048) : "memory");
                        wg_fence();
                        if (first && k == 0) wgmma_rs_n80_z<1>(acc, f[0], f[1], f[2], f[3], w); else wgmma_rs_n80<1>(acc, f[0], f[1], f[2], f[3], w + k * 160, 1);
                    } else wgmma_ss_n80<TR, 1>(acc, dA + (sl * 1152 + k * 128), w + k * 160, 1);
                    if (k % GRP == GRP - 1) { wg_commit(); wg_wait<0>(); }
                }
            };
            auto laneid = []() { uint32_t l; asm volatile("mov.u32 %0, %%laneid;" : "=r"(l)); return l; };
            auto emit = [&](uint32_t ln) {
                const uint32_t stg = smem_u32(qpark) + (wid - 16) * 2816;
                const uint32_t sa = stg + (((ln >> 3) & 1) * 8 + (ln & 7)) * 176 + (ln >> 4) * 16;
                #pragma unroll
                for (int i = 0; i < 5; i++)
                    asm volatile("stmatrix.sync.aligned.m8n8.x4.shared.b16 [%0], {%1, %2, %3, %4};" :: "r"(sa + i * 32),
                                 "r"(pack_bf16(acc[i * 8], acc[i * 8 + 1])), "r"(pack_bf16(acc[i * 8 + 2], acc[i * 8 + 3])),
                                 "r"(pack_bf16(acc[i * 8 + 4], acc[i * 8 + 5])), "r"(pack_bf16(acc[i * 8 + 6], acc[i * 8 + 7])) : "memory");
                __syncwarp();
                uint8_t* ob = (uint8_t*)(out + (size_t)tok_of((rb0 + job * 4) * 64 + (wid - 16) * 16) * DM + ns * 80);
                #pragma unroll
                for (int i = 0; i < 5; i++) {
                    const int p = ln + 32 * i, row = p / 10, col = p - row * 10;
                    uint4 v;
                    asm volatile("ld.shared.v4.b32 {%0,%1,%2,%3}, [%4];" : "=r"(v.x), "=r"(v.y), "=r"(v.z), "=r"(v.w) : "r"(stg + row * 176 + col * 16) : "memory");
                    asm volatile("st.global.v4.b32 [%0], {%1,%2,%3,%4};" :: "l"(ob + row * 2560 + col * 16), "r"(v.x), "r"(v.y), "r"(v.z), "r"(v.w) : "memory");
                }
            };
            #pragma unroll
            for (int cc = 0; cc < 10; cc++) {
                const int c = job * 15 + cc, sl = c % SR_ST;
                if (sl == 0) { dA += zero; dWa += zero; }
                item(Int<0>(), c, 4, dWa + sl * 1152, cc == 0);
                if (cc < 9) mbar_arrive_if(bar + B_SE + 8 * sl, rel);
            }
            wg_wait<0>();
            fence_regs(acc);
            mbar_arrive_if(job ? bar + B_R : bar + B_SE + 8 * (9 % SR_ST), rel);
            #pragma unroll
            for (int b = 0; b < 10; b++) { acc[4 * b] *= ga; acc[4 * b + 1] *= ga; acc[4 * b + 2] *= gb; acc[4 * b + 3] *= gb; }
            fence_regs(acc);
            TSA(1, 12 + job);
            dA += zero; dWb += zero;
            if (job == 0) {
                mbar_wait_ns<NSS>(bar + B_W, 0);
                #pragma unroll
                for (int c = 10; c < 15; c++) {
                    item(Int<1>(), c, 8, dWb + (c - 10) * 1280, false);
                    if (c < 14) mbar_arrive_if(bar + B_SE + 8 * (c % SR_ST), rel);
                }
                wg_wait<0>();
                fence_regs(acc);
                mbar_arrive_if(bar + B_SE + 8 * (14 % SR_ST), rel);
                mbar_wait_ns<NSS>(bar + B_P, 0);
                emit(laneid());
            } else {
                const uint32_t ln = laneid();
                #pragma unroll
                for (int c = 0; c < 8; c++) {
                    if (c == 0) { mbar_wait_ns<500>(bar + B_T, 0); mbar_wait_ns<100>(bar + B_X, 0); }
                    mbar_wait(bar + B_X + 8 * c, 0);
                    const uint64_t a = c < 5 ? dA + c * 640 : dA - ((K2_STR - KV_STAGE - (c - 5) * 10240) >> 4);
                    wg_fence();
                    #pragma unroll
                    for (int k = 0; k < 5; k++) wgmma_ss_n80<1, 1>(acc, a + k * 128, dWb + (c * 800 + k * 160), 1);
                    wg_commit();
                }
                wg_wait<0>();
                fence_regs(acc);
                TSA(1, 9);
                emit(ln);
            }
            TSA(1, 14 + job);
        }
        TSA_DUMP(1);
        return;
    }
    const int wg = wid >> 2, warp = wid & 3, t = lane & 3;
    const int u0 = qq * 512 + wg * 64 + warp * 16;
    uint32_t fast, c1;
    {
        const uint8_t* Q = g_XB + ((h >> 1) * 128 + (u0 >> 4)) * 1280;
        const uint4 qa = __ldcg((const uint4*)(Q + (h & 1) * 512) + lane), qc = __ldcg((const uint4*)(Q + 16 * 1280 + (h & 1) * 512) + lane);
        uint2 qb = __ldcg((const uint2*)(Q + 1024) + lane), qd = __ldcg((const uint2*)(Q + 16 * 1280 + 1024) + lane);
        __syncthreads();
        const bool isdata = (h & 1) ? t >= 2 : t < 2;
        if (!isdata) { qb = make_uint2(0u, 0u); qd = qb; }
        const uint32_t nq = hmax2b(norm2(qa.x, qa.z, qb.x, qa.y, qa.w, qb.y), norm2(qc.x, qc.z, qd.x, qc.y, qc.w, qd.y));
        TSA(1, 10);
        mbar_wait(bar + B_L, 0);
        float qlim;
        asm volatile("ld.shared.v2.b32 {%0, %1}, [%2];" : "=r"(c1), "=f"(qlim) : "r"(smem_u32(&s_lim)) : "memory");
        const bool ok = bf_lo(nq) <= qlim && bf_hi(nq) <= qlim;
        asm volatile("{\n.reg .pred p, q;\nsetp.ne.u32 p, %1, 0;\nbarrier.cta.red.and.aligned.pred q, %2, 128, p;\nselp.u32 %0, 1, 0, q;\n}"
                     : "=r"(fast) : "r"((uint32_t)ok), "r"(wg + 1) : "memory");
        fast = warp_uniform(fast);
        if (!isdata && fast) { qb.x = qb.y = qd.x = qd.y = (t & 1) ? 0x00003F80u : 0x3F803F80u; }
        const uint32_t tid = threadIdx.x - VOFF, a0 = skv + K2_WOB + tid * 16;
        asm volatile("st.shared.v4.b32 [%0], {%1,%2,%3,%4};" :: "r"(a0), "r"(qa.x), "r"(qa.y), "r"(qa.z), "r"(qa.w) : "memory");
        asm volatile("st.shared.v4.b32 [%0], {%1,%2,%3,%3};" :: "r"(a0 + 8192), "r"(qb.x), "r"(qb.y), "r"(0u) : "memory");
        qpark[0][tid] = qc; qpark[1][tid] = make_uint4(qd.x, qd.y, 0u, 0u);
    }
    asm volatile("setmaxnreg.inc.sync.aligned.u32 96;");
    const uint32_t rel = (threadIdx.x & 127) == 0;
    const uint64_t dk0 = mkdesc(skv, 128, 384, 0) + zero, dk1 = mkdesc(skv + 256, 0, 384, 0) + zero, dv0 = mkdesc(skv + 6144, 384, 128, 0) + zero;
    #pragma unroll 1
    for (int pass = 0; pass < 2; pass++) {
        uint32_t q[8];
        {
            uint32_t tid;
            asm volatile("mov.u32 %0, %%tid.x;" : "=r"(tid));
            const uint32_t a = (pass ? smem_u32(qpark) : skv + K2_WOB) + (tid - VOFF) * 16;
            asm volatile("ld.shared.v4.b32 {%0,%1,%2,%3}, [%4];" : "=r"(q[0]), "=r"(q[1]), "=r"(q[2]), "=r"(q[3]) : "r"(a) : "memory");
            asm volatile("ld.shared.v4.b32 {%0,%1,%2,%3}, [%4];" : "=r"(q[4]), "=r"(q[5]), "=r"(q[6]), "=r"(q[7]) : "r"(a + 8192) : "memory");
        }
        float o[12];
        #pragma unroll
        for (int i = 0; i < 12; i++) o[i] = 0.f;
        fence_regs(o);
        if (fast) {
            float s[32];
            uint32_t p[16];
            mbar_wait(bar + B_KVF, 0);
            TSA(1, 1 + pass * 3);
            wg_fence();
            wgmma_rs_n64_z<0>(s, q[0], q[1], q[2], q[3], dk0);
            wgmma_rs_n64<0>(s, q[4], q[5], q[6], q[7], dk1, 1);
            wg_commit();
            #pragma unroll 1
            for (int jj = 0;; jj++) {
                attn_tile<0>(s, p, o, q, c1, dk0, dk1, dv0, bar, jj ? rel : 0u, jj & 1);
                attn_tile<1>(s, p, o, q, c1, dk0, dk1, dv0, bar, rel, jj & 1);
                attn_tile<2>(s, p, o, q, c1, dk0, dk1, dv0, bar, rel, jj & 1);
                attn_tile<3>(s, p, o, q, c1, dk0, dk1, dv0, bar, rel, jj == 3 ? 2 : (jj + 1) & 1, false);
                if (jj == 3) break;
                wg_fence();
                wgmma_rs_n64_z<0>(s, q[0], q[1], q[2], q[3], dk0);
                wgmma_rs_n64<0>(s, q[4], q[5], q[6], q[7], dk1, 1);
                wg_commit();
            }
            if (pass && rel) asm volatile("red.relaxed.gpu.global.add.u32 [%0], 1;" :: "l"(&g_cnt[2 + qq * 4 + wg][h >> 2]) : "memory");
            wg_wait<0>();
            mbar_arrive_if(bar + B_KVE + 8 * (K2_ST - 1), rel);
        } else {
            float m0 = -3.0e38f, m1 = -3.0e38f;
            #pragma unroll 1
            for (int j = 0; j < 64; j++) {
                const int st = (j >> 2) % K2_ST;
                const uint32_t so = st * (KV_STAGE >> 4) + (j & 3) * 96;
                float sg[16];
                uint32_t pg[8];
                mbar_wait(bar + B_KVF + 8 * st, (j >> 4) & 1);
                wg_fence();
                wgmma_rs_n32_z<0>(sg, q[0], q[1], q[2], q[3], dk0 + so);
                wgmma_rs_n32<0>(sg, q[4], q[5], q[6], q[7], dk1 + so, 1);
                wg_commit();
                wg_wait<0>();
                fence_regs(sg);
                exp_step_max(sg, pg, o, m0, m1, POLY_PAT >> ((j & 7) * 4));
                wg_fence();
                wgmma_rs_n24<1>(o, pg[0], pg[1], pg[2], pg[3], dv0 + so, 1);
                wgmma_rs_n24<1>(o, pg[4], pg[5], pg[6], pg[7], dv0 + so + 48, 1);
                wg_commit();
                wg_wait<0>();
                fence_regs(o);
                mbar_arrive_if(bar + B_KVE + 8 * st, (j & 3) == 3 ? rel : 0u);
            }
            if (pass && rel) asm volatile("red.relaxed.gpu.global.add.u32 [%0], 1;" :: "l"(&g_cnt[2 + qq * 4 + wg][h >> 2]) : "memory");
        }
        fence_regs(o);
        TSA(1, 2 + pass * 3);
        uint32_t tid;
        asm volatile("mov.u32 %0, %%tid.x;" : "=r"(tid));
        tid -= VOFF;
        const int src = (tid & 28) + ((h & 1) ? 0 : 2);
        mbar_wait(bar + B_G, 0);
        const float* gp = gpark + pass * 256 + (tid >> 5) * 16 + ((tid & 31) >> 2);
        store_o(o, h, u0 + pass * 256, tid & 31, gp[0] * rcp(__shfl_sync(~0u, o[8], src)), gp[8] * rcp(__shfl_sync(~0u, o[10], src)));
        __syncwarp();
        mbar_arrive_if(pass ? bar + B_D : bar + B_O + 8 * wg, (tid & 31) == 0);
        TSA(1, 3 + pass * 3);
    }
    #pragma unroll 1
    for (int c = wg; c < 8; c += 4) {
        const uint32_t tid = threadIdx.x & 127;
        const uint32_t dst = skv + (c < 5 ? K2_STR + c * 10240 : KV_STAGE + (c - 5) * 10240) + tid * 16;
        mbar_wait(bar + B_H + 8 * c, 0);
        uint4 v[5];
        #pragma unroll
        for (int i = 0; i < 5; i++)
            asm volatile("ld.shared.v4.b32 {%0,%1,%2,%3}, [%4];" : "=r"(v[i].x), "=r"(v[i].y), "=r"(v[i].z), "=r"(v[i].w) : "r"(dst + i * 2048) : "memory");
        auto bad = [](const uint4& d) { return d.x == ~0u || d.y == ~0u || d.z == ~0u || d.w == ~0u; };
        if (__any_sync(~0u, bad(v[0]) || bad(v[1]) || bad(v[2]) || bad(v[3]) || bad(v[4]))) {
            const uint4* src = (const uint4*)(g_O + (36 + rb0) * 80 * 256) + c * 640 + tid;
            #pragma unroll 1
            for (int it = 0; it < (1 << 18); it++) {
                bool any = false;
                #pragma unroll
                for (int i = 0; i < 5; i++)
                    if (bad(v[i])) {
                        asm volatile("ld.relaxed.gpu.global.v4.b32 {%0,%1,%2,%3}, [%4];" : "=r"(v[i].x), "=r"(v[i].y), "=r"(v[i].z), "=r"(v[i].w) : "l"(src + i * 128) : "memory");
                        any = true;
                    }
                if (!__any_sync(~0u, any)) break;
            }
            #pragma unroll
            for (int i = 0; i < 5; i++)
                asm volatile("st.shared.v4.b32 [%0], {%1,%2,%3,%4};" :: "r"(dst + i * 2048), "r"(v[i].x), "r"(v[i].y), "r"(v[i].z), "r"(v[i].w) : "memory");
            asm volatile("fence.proxy.async.shared::cta;" ::: "memory");
            __syncwarp();
        }
        mbar_arrive_if(bar + B_X + 8 * c, lane == 0);
    }
    TSA(1, 11);
}

typedef CUresult (*EncFn)(CUtensorMap*, CUtensorMapDataType, cuuint32_t, void*, const cuuint64_t*, const cuuint64_t*, const cuuint32_t*,
                          const cuuint32_t*, CUtensorMapInterleave, CUtensorMapSwizzle, CUtensorMapL2promotion, CUtensorMapFloatOOBfill);

static void make_map(EncFn enc, CUtensorMap* tm, const void* base, int rank, const cuuint64_t* dims, const cuuint64_t* strides,
                     const cuuint32_t* box, CUtensorMapSwizzle swz) {
    const cuuint32_t es[4] = {1, 1, 1, 1};
    enc(tm, CU_TENSOR_MAP_DATA_TYPE_BFLOAT16, rank, (void*)base, dims, strides, box, es, CU_TENSOR_MAP_INTERLEAVE_NONE, swz,
        CU_TENSOR_MAP_L2_PROMOTION_L2_128B, CU_TENSOR_MAP_FLOAT_OOB_FILL_NONE);
}

extern "C" void kernel_launch(void* const* d_in, const int* in_sizes, int n_in, void* d_out, int out_size) {
    const __nv_bfloat16* x = (const __nv_bfloat16*)d_in[0];
    const void *wqa = d_in[1], *woa = d_in[2], *wqb = d_in[4], *wob = d_in[5];
    const __nv_bfloat16* gw = (const __nv_bfloat16*)d_in[6];
    static EncFn enc = nullptr;
    if (!enc) {
        void* fn = nullptr; cudaDriverEntryPointQueryResult qr;
        cudaGetDriverEntryPoint("cuTensorMapEncodeTiled", &fn, cudaEnableDefault, &qr);
        enc = (EncFn)fn;
        cudaFuncSetAttribute(k1_qkv, cudaFuncAttributeMaxDynamicSharedMemorySize, K1_SMEM);
        cudaFuncSetAttribute(k2_attn, cudaFuncAttributeMaxDynamicSharedMemorySize, K2_SMEM);
    }
    CUtensorMap tmx, tmwb, tmwa, tmwg, tmwn;
    { cuuint64_t d[2] = {1280, 1024}, s[1] = {2560}; cuuint32_t b[2] = {64, 128}; make_map(enc, &tmx, x, 2, d, s, b, CU_TENSOR_MAP_SWIZZLE_128B); }
    { cuuint64_t d[2] = {1920, 640}, s[1] = {3840}; cuuint32_t b[2] = {64, 32}, n[2] = {48, 32};
      make_map(enc, &tmwa, wqa, 2, d, s, b, CU_TENSOR_MAP_SWIZZLE_128B); make_map(enc, &tmwb, wqb, 2, d, s, b, CU_TENSOR_MAP_SWIZZLE_128B);
      make_map(enc, &tmwn, wqb, 2, d, s, n, CU_TENSOR_MAP_SWIZZLE_128B); }
    { void* pg = nullptr; cudaGetSymbolAddress(&pg, g_Wg);
      cuuint64_t d[2] = {512, 640}, s[1] = {1024}; cuuint32_t b[2] = {48, 32}; make_map(enc, &tmwg, pg, 2, d, s, b, CU_TENSOR_MAP_SWIZZLE_128B); }
    k1_qkv<<<132, 384, K1_SMEM, cudaStreamPerThread>>>(tmx, tmwb, tmwa, tmwg, tmwn, x, gw, (const uint8_t*)wqb, (const uint8_t*)wqa, (const uint8_t*)woa, (uint64_t)0);
    {
        cudaLaunchConfig_t cfg = {};
        cfg.gridDim = dim3(132); cfg.blockDim = dim3(768); cfg.dynamicSmemBytes = K2_SMEM; cfg.stream = cudaStreamPerThread;
        cudaLaunchAttribute at[1];
        at[0].id = cudaLaunchAttributeProgrammaticStreamSerialization; at[0].val.programmaticStreamSerializationAllowed = 1;
        cfg.attrs = at; cfg.numAttrs = 1;
        cudaLaunchKernelEx(&cfg, k2_attn, (__nv_bfloat16*)d_out, (const uint8_t*)wob, (uint64_t)0);
    }
}
```
